```python
import torch

def _softmax(x, axis=-1):
    return torch.softmax(x, dim=axis)
def _gelu(x):
    return torch.nn.functional.gelu(x, approximate="tanh")
def _silu(x):
    return torch.nn.functional.silu(x)
def _sigmoid(x):
    return torch.sigmoid(x)
def _layernorm(x, axis=-1, eps=1e-5):
    m = x.mean(dim=axis, keepdim=True)
    v = x.var(dim=axis, keepdim=True, unbiased=False)
    return (x - m) / torch.sqrt(v + eps)
def _scatter_add(tgt, idx, src, axis=0):
    return tgt.clone().index_add_(axis, idx, src)
def _segment_sum(src, seg, n):
    out = torch.zeros((n,) + src.shape[1:], dtype=src.dtype)
    return out.index_add_(0, seg, src)
def _pad(x, pw):
    flat = tuple(v for pair in reversed(pw) for v in pair)
    return torch.nn.functional.pad(x, flat)

kernel_name = 'interleave_layers__softmax_full_mha__mixer_channel_mlp__prompt'

def setup_inputs():

    _w = (lambda a: (lambda t: t.to(torch.bfloat16) if t.is_floating_point() else t)(torch.as_tensor(a)))
    def _A_setup():
        B, S, D = 1, 2048, 640
        return {
            "x": _w((lambda *s: torch.randn(*s, dtype=torch.bfloat16) * 0.05)(B, S, D)),
            "wqkv": _w((lambda *s: torch.randn(*s, dtype=torch.bfloat16) * 0.05)(D, 3 * D)),
            "wo": _w((lambda *s: torch.randn(*s, dtype=torch.bfloat16) * 0.05)(D, D)),
        }
    _A_in = _A_setup()

    def _B_setup():
        B, S, D, F = 1, 2048, 640, 1728
        return {
            "x": _w((lambda *s: torch.randn(*s, dtype=torch.bfloat16) * 0.05)(B, S, D)),
            "w1": _w((lambda *s: torch.randn(*s, dtype=torch.bfloat16) * 3.2)(D, F) * (D ** -0.5)),
            "b1": _w((lambda *s: torch.randn(*s, dtype=torch.bfloat16) * 0.8)(F)),
            "w2": _w((lambda *s: torch.randn(*s, dtype=torch.bfloat16) * 0.2)(F, D) * (F ** -0.5)),
            "b2": _w((lambda *s: torch.randn(*s, dtype=torch.bfloat16) * 0.2)(D)),
        }
    _B_in = _B_setup()

    return {
        "A_x": _A_in["x"],
        "A_wqkv": _A_in["wqkv"],
        "A_wo": _A_in["wo"],
        "B_x": _B_in["x"],
        "B_w1": _B_in["w1"],
        "B_b1": _B_in["b1"],
        "B_w2": _B_in["w2"],
        "B_b2": _B_in["b2"],
    }

def reference(A_x, A_wqkv, A_wo, B_x, B_w1, B_b1, B_w2, B_b2):
    def _A_ref(x, wqkv, wo):
        B, S, D = x.shape
        H = 32; Dh = D // H
        qkv = (lambda x, *d: x.permute(*d))((x @ wqkv).reshape(B, S, 3, H, Dh), 2, 0, 3, 1, 4)
        q, k, v = qkv[0], qkv[1], qkv[2]
        scale = Dh ** -0.5
        scores = torch.einsum("bhqd,bhkd->bhqk", q, k) * scale
        p = _softmax(scores, axis=-1)
        o = torch.einsum("bhqk,bhkd->bhqd", p, v)
        return (lambda x, *d: x.permute(*d))(o, 0, 2, 1, 3).reshape(B, S, D) @ wo

    def _B_ref(x, w1, b1, w2, b2):
        y = _layernorm(x, axis=-1)
        h = _gelu(torch.einsum("bsd,df->bsf", y, w1) + b1)
        return torch.einsum("bsf,fd->bsd", h, w2) + b2

    x = A_x
    x = x + _A_ref(_layernorm(x, axis=-1), A_wqkv, A_wo)
    x = x + _B_ref(_layernorm(x, axis=-1), B_w1, B_b1, B_w2, B_b2)
    x = x + _A_ref(_layernorm(x, axis=-1), A_wqkv, A_wo)
    x = x + _B_ref(_layernorm(x, axis=-1), B_w1, B_b1, B_w2, B_b2)
    return x
```

```cpp
#include <cuda_runtime.h>
#include <cuda_bf16.h>
#include <cuda.h>
#include <stdint.h>

#define CHAIN_FUSED 1

typedef __nv_bfloat16 bf16;

constexpr int SEQ = 2048, DM = 640, FF = 1728;
constexpr float LN_EPS = 1e-5f;
constexpr int HEAD_BYTES = 98304;
constexpr uint32_t MUFU_MASK = 0x4949u;
__host__ __device__ constexpr bool is_mufu(int g) { return (MUFU_MASK >> (g & 15)) & 1u; }

__device__ __align__(1024) bf16 g_qkv[96 * (HEAD_BYTES / 2)];
__device__ __align__(1024) bf16 g_o[SEQ * DM];
__device__ __align__(1024) bf16 g_x1[SEQ * DM];
__device__ __align__(1024) bf16 g_x2[SEQ * DM];
__device__ __align__(1024) bf16 g_h[SEQ * FF];
__device__ __align__(64) float2 g_st0[SEQ];
__device__ __align__(64) float2 g_st1[SEQ * 8];
__device__ __align__(64) float2 g_st2[SEQ * 8];
__device__ __align__(64) float g_csp_qkv[32 * 1920];
__device__ __align__(64) float g_csp_w1[32 * FF];
__device__ __align__(128) unsigned int g_flags[192];

__device__ __forceinline__ uint32_t smem_u32(const void* p) { return (uint32_t)__cvta_generic_to_shared(p); }
__device__ __forceinline__ void mbar_init(uint32_t bar, int cnt) { asm volatile("mbarrier.init.shared::cta.b64 [%0], %1;" ::"r"(bar), "r"(cnt) : "memory"); }
__device__ __forceinline__ void mbar_expect_tx(uint32_t bar, uint32_t bytes) { asm volatile("mbarrier.arrive.expect_tx.shared::cta.b64 _, [%0], %1;" ::"r"(bar), "r"(bytes) : "memory"); }
__device__ __forceinline__ void mbar_arrive(uint32_t bar) { asm volatile("mbarrier.arrive.shared::cta.b64 _, [%0];" ::"r"(bar) : "memory"); }
__device__ __forceinline__ bool mbar_try(uint32_t bar, uint32_t parity) {
  uint32_t ok;
  asm volatile("{\n.reg .pred p;\nmbarrier.try_wait.parity.shared::cta.b64 p, [%1], %2;\nselp.u32 %0, 1, 0, p;\n}\n" : "=r"(ok) : "r"(bar), "r"(parity) : "memory");
  return ok != 0;
}
__device__ __forceinline__ void mbar_wait(uint32_t bar, uint32_t parity) {
  if (mbar_try(bar, parity)) return;
  for (int it = 0; it < (1 << 22); it++)
    if (mbar_try(bar, parity)) return;
  __trap();
}
__device__ __forceinline__ void flag_wait(const unsigned int* f, unsigned int target) {
  unsigned int v;
  for (int it = 0; it < (1 << 22); it++) {
    asm volatile("ld.acquire.gpu.global.u32 %0, [%1];" : "=r"(v) : "l"(f) : "memory");
    if (v >= target) return;
  }
  __trap();
}
__device__ __forceinline__ void flag_signal(unsigned int* f) { asm volatile("red.release.gpu.global.add.u32 [%0], 1;" ::"l"(f) : "memory"); }
__device__ __forceinline__ void fence_async_global() { asm volatile("fence.proxy.async.global;" ::: "memory"); }
__device__ __forceinline__ void pdl_wait() { asm volatile("griddepcontrol.wait;" ::: "memory"); }
__device__ __forceinline__ void pdl_launch() { asm volatile("griddepcontrol.launch_dependents;" ::: "memory"); }
__device__ __forceinline__ void named_bar(int id, int n) { asm volatile("bar.sync %0, %1;" ::"r"(id), "r"(n) : "memory"); }
__device__ __forceinline__ void bulk_g2s(uint32_t dst, const void* src, uint32_t bytes, uint32_t bar) {
  asm volatile("cp.async.bulk.shared::cluster.global.mbarrier::complete_tx::bytes [%0], [%1], %2, [%3];" ::"r"(dst), "l"(src), "r"(bytes), "r"(bar) : "memory");
}
__device__ __forceinline__ void prefetch_l2(const void* src, uint32_t bytes) { asm volatile("cp.async.bulk.prefetch.L2.global [%0], %1;" ::"l"(src), "r"(bytes) : "memory"); }
__device__ __forceinline__ void tma_2d(uint32_t dst, const CUtensorMap* m, int c0, int c1, uint32_t bar) {
  asm volatile("cp.async.bulk.tensor.2d.shared::cluster.global.mbarrier::complete_tx::bytes [%0], [%1, {%3, %4}], [%2];" ::"r"(dst), "l"(m), "r"(bar), "r"(c0), "r"(c1) : "memory");
}
__device__ __forceinline__ void tma_3d(uint32_t dst, const CUtensorMap* m, int c0, int c1, int c2, uint32_t bar) {
  asm volatile("cp.async.bulk.tensor.3d.shared::cluster.global.mbarrier::complete_tx::bytes [%0], [%1, {%3, %4, %5}], [%2];" ::"r"(dst), "l"(m), "r"(bar), "r"(c0), "r"(c1), "r"(c2) : "memory");
}
__device__ __forceinline__ void wg_fence() { asm volatile("wgmma.fence.sync.aligned;" ::: "memory"); }
__device__ __forceinline__ void wg_commit() { asm volatile("wgmma.commit_group.sync.aligned;" ::: "memory"); }
template <int N> __device__ __forceinline__ void wg_wait() { asm volatile("wgmma.wait_group.sync.aligned %0;" ::"n"(N) : "memory"); }
template <int N> __device__ __forceinline__ void fence_regs(float (&d)[N]) {
#pragma unroll
  for (int i = 0; i < N; i++) asm volatile("" : "+f"(d[i])::"memory");
}
template <int N> __device__ __forceinline__ void fence_regs(uint32_t (&d)[N]) {
#pragma unroll
  for (int i = 0; i < N; i++) asm volatile("" : "+r"(d[i])::"memory");
}
__device__ __forceinline__ uint64_t mk_desc(uint32_t addr, uint32_t lbo, uint32_t sbo, uint64_t swz) {
  return (uint64_t)((addr & 0x3FFFF) >> 4) | ((uint64_t)(lbo >> 4) << 16) | ((uint64_t)(sbo >> 4) << 32) | (swz << 62);
}
__device__ __forceinline__ uint32_t pack_bf16(float lo, float hi) {
  uint32_t r;
  asm("cvt.rn.bf16x2.f32 %0, %1, %2;" : "=r"(r) : "f"(hi), "f"(lo));
  return r;
}
__device__ __forceinline__ float bf_lo(uint32_t v) { return __uint_as_float(v << 16); }
__device__ __forceinline__ float bf_hi(uint32_t v) { return __uint_as_float(v & 0xFFFF0000u); }
__device__ __forceinline__ float ex2(float x) { float r; asm("ex2.approx.ftz.f32 %0, %1;" : "=f"(r) : "f"(x)); return r; }

template<int TB> __device__ __forceinline__ void wgmma_rs_n24(float (&d)[12], uint32_t a0, uint32_t a1, uint32_t a2, uint32_t a3, uint64_t db, int sd) {
  asm volatile("{\n.reg .pred p;\nsetp.ne.b32 p, %17, 0;\n"
    "wgmma.mma_async.sync.aligned.m64n24k16.f32.bf16.bf16 "
    "{%0,%1,%2,%3,%4,%5,%6,%7,%8,%9,%10,%11}, "
    "{%12,%13,%14,%15}, %16, p, 1, 1, %18;\n}\n"
    : "+f"(d[0]),"+f"(d[1]),"+f"(d[2]),"+f"(d[3]),"+f"(d[4]),"+f"(d[5]),"+f"(d[6]),"+f"(d[7]),"+f"(d[8]),"+f"(d[9]),"+f"(d[10]),"+f"(d[11])
    : "r"(a0), "r"(a1), "r"(a2), "r"(a3), "l"(db), "r"(sd), "n"(TB));
}
template<int TB> __device__ __forceinline__ void wgmma_rs_n64(float (&d)[32], uint32_t a0, uint32_t a1, uint32_t a2, uint32_t a3, uint64_t db, int sd) {
  asm volatile("{\n.reg .pred p;\nsetp.ne.b32 p, %37, 0;\n"
    "wgmma.mma_async.sync.aligned.m64n64k16.f32.bf16.bf16 "
    "{%0,%1,%2,%3,%4,%5,%6,%7,%8,%9,%10,%11,%12,%13,%14,%15,%16,%17,%18,%19,%20,%21,%22,%23,%24,%25,%26,%27,%28,%29,%30,%31}, "
    "{%32,%33,%34,%35}, %36, p, 1, 1, %38;\n}\n"
    : "+f"(d[0]),"+f"(d[1]),"+f"(d[2]),"+f"(d[3]),"+f"(d[4]),"+f"(d[5]),"+f"(d[6]),"+f"(d[7]),"+f"(d[8]),"+f"(d[9]),"+f"(d[10]),"+f"(d[11]),"+f"(d[12]),"+f"(d[13]),"+f"(d[14]),"+f"(d[15]),"+f"(d[16]),"+f"(d[17]),"+f"(d[18]),"+f"(d[19]),"+f"(d[20]),"+f"(d[21]),"+f"(d[22]),"+f"(d[23]),"+f"(d[24]),"+f"(d[25]),"+f"(d[26]),"+f"(d[27]),"+f"(d[28]),"+f"(d[29]),"+f"(d[30]),"+f"(d[31])
    : "r"(a0), "r"(a1), "r"(a2), "r"(a3), "l"(db), "r"(sd), "n"(TB));
}
template<int TB> __device__ __forceinline__ void wgmma_rs_n128(float (&d)[64], uint32_t a0, uint32_t a1, uint32_t a2, uint32_t a3, uint64_t db, int sd) {
  asm volatile("{\n.reg .pred p;\nsetp.ne.b32 p, %69, 0;\n"
    "wgmma.mma_async.sync.aligned.m64n128k16.f32.bf16.bf16 "
    "{%0,%1,%2,%3,%4,%5,%6,%7,%8,%9,%10,%11,%12,%13,%14,%15,%16,%17,%18,%19,%20,%21,%22,%23,%24,%25,%26,%27,%28,%29,%30,%31,%32,%33,%34,%35,%36,%37,%38,%39,%40,%41,%42,%43,%44,%45,%46,%47,%48,%49,%50,%51,%52,%53,%54,%55,%56,%57,%58,%59,%60,%61,%62,%63}, "
    "{%64,%65,%66,%67}, %68, p, 1, 1, %70;\n}\n"
    : "+f"(d[0]),"+f"(d[1]),"+f"(d[2]),"+f"(d[3]),"+f"(d[4]),"+f"(d[5]),"+f"(d[6]),"+f"(d[7]),"+f"(d[8]),"+f"(d[9]),"+f"(d[10]),"+f"(d[11]),"+f"(d[12]),"+f"(d[13]),"+f"(d[14]),"+f"(d[15]),"+f"(d[16]),"+f"(d[17]),"+f"(d[18]),"+f"(d[19]),"+f"(d[20]),"+f"(d[21]),"+f"(d[22]),"+f"(d[23]),"+f"(d[24]),"+f"(d[25]),"+f"(d[26]),"+f"(d[27]),"+f"(d[28]),"+f"(d[29]),"+f"(d[30]),"+f"(d[31]),"+f"(d[32]),"+f"(d[33]),"+f"(d[34]),"+f"(d[35]),"+f"(d[36]),"+f"(d[37]),"+f"(d[38]),"+f"(d[39]),"+f"(d[40]),"+f"(d[41]),"+f"(d[42]),"+f"(d[43]),"+f"(d[44]),"+f"(d[45]),"+f"(d[46]),"+f"(d[47]),"+f"(d[48]),"+f"(d[49]),"+f"(d[50]),"+f"(d[51]),"+f"(d[52]),"+f"(d[53]),"+f"(d[54]),"+f"(d[55]),"+f"(d[56]),"+f"(d[57]),"+f"(d[58]),"+f"(d[59]),"+f"(d[60]),"+f"(d[61]),"+f"(d[62]),"+f"(d[63])
    : "r"(a0), "r"(a1), "r"(a2), "r"(a3), "l"(db), "r"(sd), "n"(TB));
}
__device__ __forceinline__ void wgmma_ss(float (&d)[40], uint64_t da, uint64_t db, int sd) {
  asm volatile("{\n.reg .pred p;\nsetp.ne.b32 p, %42, 0;\n"
    "wgmma.mma_async.sync.aligned.m64n80k16.f32.bf16.bf16 "
    "{%0,%1,%2,%3,%4,%5,%6,%7,%8,%9,%10,%11,%12,%13,%14,%15,%16,%17,%18,%19,%20,%21,%22,%23,%24,%25,%26,%27,%28,%29,%30,%31,%32,%33,%34,%35,%36,%37,%38,%39}, "
    "%40, %41, p, 1, 1, 0, 1;\n}\n"
    : "+f"(d[0]),"+f"(d[1]),"+f"(d[2]),"+f"(d[3]),"+f"(d[4]),"+f"(d[5]),"+f"(d[6]),"+f"(d[7]),"+f"(d[8]),"+f"(d[9]),"+f"(d[10]),"+f"(d[11]),"+f"(d[12]),"+f"(d[13]),"+f"(d[14]),"+f"(d[15]),"+f"(d[16]),"+f"(d[17]),"+f"(d[18]),"+f"(d[19]),"+f"(d[20]),"+f"(d[21]),"+f"(d[22]),"+f"(d[23]),"+f"(d[24]),"+f"(d[25]),"+f"(d[26]),"+f"(d[27]),"+f"(d[28]),"+f"(d[29]),"+f"(d[30]),"+f"(d[31]),"+f"(d[32]),"+f"(d[33]),"+f"(d[34]),"+f"(d[35]),"+f"(d[36]),"+f"(d[37]),"+f"(d[38]),"+f"(d[39])
    : "l"(da), "l"(db), "r"(sd));
}
__device__ __forceinline__ void wgmma_ss(float (&d)[80], uint64_t da, uint64_t db, int sd) {
  asm volatile("{\n.reg .pred p;\nsetp.ne.b32 p, %82, 0;\n"
    "wgmma.mma_async.sync.aligned.m64n160k16.f32.bf16.bf16 "
    "{%0,%1,%2,%3,%4,%5,%6,%7,%8,%9,%10,%11,%12,%13,%14,%15,%16,%17,%18,%19,%20,%21,%22,%23,%24,%25,%26,%27,%28,%29,%30,%31,%32,%33,%34,%35,%36,%37,%38,%39,%40,%41,%42,%43,%44,%45,%46,%47,%48,%49,%50,%51,%52,%53,%54,%55,%56,%57,%58,%59,%60,%61,%62,%63,%64,%65,%66,%67,%68,%69,%70,%71,%72,%73,%74,%75,%76,%77,%78,%79}, "
    "%80, %81, p, 1, 1, 0, 1;\n}\n"
    : "+f"(d[0]),"+f"(d[1]),"+f"(d[2]),"+f"(d[3]),"+f"(d[4]),"+f"(d[5]),"+f"(d[6]),"+f"(d[7]),"+f"(d[8]),"+f"(d[9]),"+f"(d[10]),"+f"(d[11]),"+f"(d[12]),"+f"(d[13]),"+f"(d[14]),"+f"(d[15]),"+f"(d[16]),"+f"(d[17]),"+f"(d[18]),"+f"(d[19]),"+f"(d[20]),"+f"(d[21]),"+f"(d[22]),"+f"(d[23]),"+f"(d[24]),"+f"(d[25]),"+f"(d[26]),"+f"(d[27]),"+f"(d[28]),"+f"(d[29]),"+f"(d[30]),"+f"(d[31]),"+f"(d[32]),"+f"(d[33]),"+f"(d[34]),"+f"(d[35]),"+f"(d[36]),"+f"(d[37]),"+f"(d[38]),"+f"(d[39]),"+f"(d[40]),"+f"(d[41]),"+f"(d[42]),"+f"(d[43]),"+f"(d[44]),"+f"(d[45]),"+f"(d[46]),"+f"(d[47]),"+f"(d[48]),"+f"(d[49]),"+f"(d[50]),"+f"(d[51]),"+f"(d[52]),"+f"(d[53]),"+f"(d[54]),"+f"(d[55]),"+f"(d[56]),"+f"(d[57]),"+f"(d[58]),"+f"(d[59]),"+f"(d[60]),"+f"(d[61]),"+f"(d[62]),"+f"(d[63]),"+f"(d[64]),"+f"(d[65]),"+f"(d[66]),"+f"(d[67]),"+f"(d[68]),"+f"(d[69]),"+f"(d[70]),"+f"(d[71]),"+f"(d[72]),"+f"(d[73]),"+f"(d[74]),"+f"(d[75]),"+f"(d[76]),"+f"(d[77]),"+f"(d[78]),"+f"(d[79])
    : "l"(da), "l"(db), "r"(sd));
}
__device__ __forceinline__ void wgmma_ss(float (&d)[108], uint64_t da, uint64_t db, int sd) {
  asm volatile("{\n.reg .pred p;\nsetp.ne.b32 p, %110, 0;\n"
    "wgmma.mma_async.sync.aligned.m64n216k16.f32.bf16.bf16 "
    "{%0,%1,%2,%3,%4,%5,%6,%7,%8,%9,%10,%11,%12,%13,%14,%15,%16,%17,%18,%19,%20,%21,%22,%23,%24,%25,%26,%27,%28,%29,%30,%31,%32,%33,%34,%35,%36,%37,%38,%39,%40,%41,%42,%43,%44,%45,%46,%47,%48,%49,%50,%51,%52,%53,%54,%55,%56,%57,%58,%59,%60,%61,%62,%63,%64,%65,%66,%67,%68,%69,%70,%71,%72,%73,%74,%75,%76,%77,%78,%79,%80,%81,%82,%83,%84,%85,%86,%87,%88,%89,%90,%91,%92,%93,%94,%95,%96,%97,%98,%99,%100,%101,%102,%103,%104,%105,%106,%107}, "
    "%108, %109, p, 1, 1, 0, 1;\n}\n"
    : "+f"(d[0]),"+f"(d[1]),"+f"(d[2]),"+f"(d[3]),"+f"(d[4]),"+f"(d[5]),"+f"(d[6]),"+f"(d[7]),"+f"(d[8]),"+f"(d[9]),"+f"(d[10]),"+f"(d[11]),"+f"(d[12]),"+f"(d[13]),"+f"(d[14]),"+f"(d[15]),"+f"(d[16]),"+f"(d[17]),"+f"(d[18]),"+f"(d[19]),"+f"(d[20]),"+f"(d[21]),"+f"(d[22]),"+f"(d[23]),"+f"(d[24]),"+f"(d[25]),"+f"(d[26]),"+f"(d[27]),"+f"(d[28]),"+f"(d[29]),"+f"(d[30]),"+f"(d[31]),"+f"(d[32]),"+f"(d[33]),"+f"(d[34]),"+f"(d[35]),"+f"(d[36]),"+f"(d[37]),"+f"(d[38]),"+f"(d[39]),"+f"(d[40]),"+f"(d[41]),"+f"(d[42]),"+f"(d[43]),"+f"(d[44]),"+f"(d[45]),"+f"(d[46]),"+f"(d[47]),"+f"(d[48]),"+f"(d[49]),"+f"(d[50]),"+f"(d[51]),"+f"(d[52]),"+f"(d[53]),"+f"(d[54]),"+f"(d[55]),"+f"(d[56]),"+f"(d[57]),"+f"(d[58]),"+f"(d[59]),"+f"(d[60]),"+f"(d[61]),"+f"(d[62]),"+f"(d[63]),"+f"(d[64]),"+f"(d[65]),"+f"(d[66]),"+f"(d[67]),"+f"(d[68]),"+f"(d[69]),"+f"(d[70]),"+f"(d[71]),"+f"(d[72]),"+f"(d[73]),"+f"(d[74]),"+f"(d[75]),"+f"(d[76]),"+f"(d[77]),"+f"(d[78]),"+f"(d[79]),"+f"(d[80]),"+f"(d[81]),"+f"(d[82]),"+f"(d[83]),"+f"(d[84]),"+f"(d[85]),"+f"(d[86]),"+f"(d[87]),"+f"(d[88]),"+f"(d[89]),"+f"(d[90]),"+f"(d[91]),"+f"(d[92]),"+f"(d[93]),"+f"(d[94]),"+f"(d[95]),"+f"(d[96]),"+f"(d[97]),"+f"(d[98]),"+f"(d[99]),"+f"(d[100]),"+f"(d[101]),"+f"(d[102]),"+f"(d[103]),"+f"(d[104]),"+f"(d[105]),"+f"(d[106]),"+f"(d[107])
    : "l"(da), "l"(db), "r"(sd));
}
__device__ __forceinline__ void wgmma_ss(float (&d)[120], uint64_t da, uint64_t db, int sd) {
  asm volatile("{\n.reg .pred p;\nsetp.ne.b32 p, %122, 0;\n"
    "wgmma.mma_async.sync.aligned.m64n240k16.f32.bf16.bf16 "
    "{%0,%1,%2,%3,%4,%5,%6,%7,%8,%9,%10,%11,%12,%13,%14,%15,%16,%17,%18,%19,%20,%21,%22,%23,%24,%25,%26,%27,%28,%29,%30,%31,%32,%33,%34,%35,%36,%37,%38,%39,%40,%41,%42,%43,%44,%45,%46,%47,%48,%49,%50,%51,%52,%53,%54,%55,%56,%57,%58,%59,%60,%61,%62,%63,%64,%65,%66,%67,%68,%69,%70,%71,%72,%73,%74,%75,%76,%77,%78,%79,%80,%81,%82,%83,%84,%85,%86,%87,%88,%89,%90,%91,%92,%93,%94,%95,%96,%97,%98,%99,%100,%101,%102,%103,%104,%105,%106,%107,%108,%109,%110,%111,%112,%113,%114,%115,%116,%117,%118,%119}, "
    "%120, %121, p, 1, 1, 0, 1;\n}\n"
    : "+f"(d[0]),"+f"(d[1]),"+f"(d[2]),"+f"(d[3]),"+f"(d[4]),"+f"(d[5]),"+f"(d[6]),"+f"(d[7]),"+f"(d[8]),"+f"(d[9]),"+f"(d[10]),"+f"(d[11]),"+f"(d[12]),"+f"(d[13]),"+f"(d[14]),"+f"(d[15]),"+f"(d[16]),"+f"(d[17]),"+f"(d[18]),"+f"(d[19]),"+f"(d[20]),"+f"(d[21]),"+f"(d[22]),"+f"(d[23]),"+f"(d[24]),"+f"(d[25]),"+f"(d[26]),"+f"(d[27]),"+f"(d[28]),"+f"(d[29]),"+f"(d[30]),"+f"(d[31]),"+f"(d[32]),"+f"(d[33]),"+f"(d[34]),"+f"(d[35]),"+f"(d[36]),"+f"(d[37]),"+f"(d[38]),"+f"(d[39]),"+f"(d[40]),"+f"(d[41]),"+f"(d[42]),"+f"(d[43]),"+f"(d[44]),"+f"(d[45]),"+f"(d[46]),"+f"(d[47]),"+f"(d[48]),"+f"(d[49]),"+f"(d[50]),"+f"(d[51]),"+f"(d[52]),"+f"(d[53]),"+f"(d[54]),"+f"(d[55]),"+f"(d[56]),"+f"(d[57]),"+f"(d[58]),"+f"(d[59]),"+f"(d[60]),"+f"(d[61]),"+f"(d[62]),"+f"(d[63]),"+f"(d[64]),"+f"(d[65]),"+f"(d[66]),"+f"(d[67]),"+f"(d[68]),"+f"(d[69]),"+f"(d[70]),"+f"(d[71]),"+f"(d[72]),"+f"(d[73]),"+f"(d[74]),"+f"(d[75]),"+f"(d[76]),"+f"(d[77]),"+f"(d[78]),"+f"(d[79]),"+f"(d[80]),"+f"(d[81]),"+f"(d[82]),"+f"(d[83]),"+f"(d[84]),"+f"(d[85]),"+f"(d[86]),"+f"(d[87]),"+f"(d[88]),"+f"(d[89]),"+f"(d[90]),"+f"(d[91]),"+f"(d[92]),"+f"(d[93]),"+f"(d[94]),"+f"(d[95]),"+f"(d[96]),"+f"(d[97]),"+f"(d[98]),"+f"(d[99]),"+f"(d[100]),"+f"(d[101]),"+f"(d[102]),"+f"(d[103]),"+f"(d[104]),"+f"(d[105]),"+f"(d[106]),"+f"(d[107]),"+f"(d[108]),"+f"(d[109]),"+f"(d[110]),"+f"(d[111]),"+f"(d[112]),"+f"(d[113]),"+f"(d[114]),"+f"(d[115]),"+f"(d[116]),"+f"(d[117]),"+f"(d[118]),"+f"(d[119])
    : "l"(da), "l"(db), "r"(sd));
}

constexpr int PH_WO = 1, PH_W1 = 2, PH_W2 = 4, PH_QKV = 8;
constexpr int SA = 4, SB = 5;
constexpr int A_STAGE = 16384, B_STAGE = 32768;
constexpr int SM_B = SA * A_STAGE;
constexpr int SM_CS = SM_B + SB * B_STAGE;
constexpr int SM_B1 = SM_CS + 960;
constexpr int SM_ROW = SM_B1 + 864;
constexpr int SM_BAR = SM_ROW + 1024;
constexpr int CHAIN_SMEM = SM_BAR + 192;
constexpr int CHAIN_THREADS = 352;

struct alignas(64) ChainParams {
  CUtensorMap a_o, a_x1, a_h, a_xq;
  CUtensorMap b_wo, b_w1, b_w2, b_wqkv;
  const bf16* xres;
  bf16* x2out;
  const bf16 *b1, *b2, *wqkv, *w1;
  unsigned int* flags;
};

struct Ring { uint32_t s, ph; };
template <int N> __device__ __forceinline__ void ring_adv(Ring& r) { if (++r.s == N) { r.s = 0; r.ph ^= 1; } }

template <int KT, int KPS, int NBOX>
__device__ __forceinline__ void produce_b(const CUtensorMap* m, uint32_t sb, uint32_t bars, int j, Ring& r) {
  constexpr int NST = (KT + KPS - 1) / KPS;
#pragma unroll 1
  for (int st = 0; st < NST; st++) {
    const uint32_t full = bars + (2 * SA + r.s) * 8, empty = bars + (2 * SA + SB + r.s) * 8;
    mbar_wait(empty, r.ph ^ 1);
    const int nk = (KT - st * KPS) < KPS ? (KT - st * KPS) : KPS;
    mbar_expect_tx(full, nk * NBOX * 8192);
    for (int kk = 0; kk < nk; kk++)
#pragma unroll
      for (int b = 0; b < NBOX; b++) tma_3d(sb + r.s * B_STAGE + (kk * NBOX + b) * 8192, m, b * 64, j, (st * KPS + kk) * 64, full);
    ring_adv<SB>(r);
  }
}
template <int KT>
__device__ __forceinline__ void produce_a(const CUtensorMap* m, uint32_t sa, uint32_t bars, int i, Ring& r) {
#pragma unroll 1
  for (int kt = 0; kt < KT; kt++) {
    const uint32_t full = bars + r.s * 8, empty = bars + (SA + r.s) * 8;
    mbar_wait(empty, r.ph ^ 1);
    mbar_expect_tx(full, A_STAGE);
    tma_2d(sa + r.s * A_STAGE, m, kt * 64, i * 128, full);
    ring_adv<SA>(r);
  }
}
template <int BN, int KT, int KPS, int NBOX>
__device__ __forceinline__ void mainloop(float (&acc)[BN / 2], uint32_t sbase, uint32_t bars, int wg, int lane, Ring& ra, Ring& rb) {
  uint32_t relA = 0, relB = 0;
#pragma unroll 1
  for (int kt = 0; kt < KT; kt++) {
    const int kk = (KPS == 1) ? 0 : (kt % KPS);
    if (kk == 0) mbar_wait(bars + (2 * SA + rb.s) * 8, rb.ph);
    mbar_wait(bars + ra.s * 8, ra.ph);
    const uint64_t da = mk_desc(sbase + ra.s * A_STAGE + wg * 8192, 16, 1024, 1);
    const uint64_t db = mk_desc(sbase + SM_B + rb.s * B_STAGE + kk * (NBOX * 8192), 8192, 1024, 1);
    wg_fence();
#pragma unroll
    for (int k = 0; k < 4; k++) wgmma_ss(acc, da + k * 2, db + k * 128, (kt | k) != 0);
    wg_commit();
    wg_wait<1>();
    if (lane == 0) { if (relA) mbar_arrive(relA); if (relB) mbar_arrive(relB); }
    relA = bars + (SA + ra.s) * 8;
    ring_adv<SA>(ra);
    if (kk == KPS - 1 || kt == KT - 1) { relB = bars + (2 * SA + SB + rb.s) * 8; ring_adv<SB>(rb); } else relB = 0;
  }
  wg_wait<0>();
  fence_regs(acc);
  if (lane == 0) { mbar_arrive(relA); mbar_arrive(relB); }
}

template <bool BIAS>
__device__ __forceinline__ void epi_resid(const float (&acc)[40], const uint32_t (&res)[20], const bf16* bias, bf16* out, float2* st,
                                          int row0, int j, int lane) {
  const int q = lane & 3;
  uint32_t* o0 = (uint32_t*)(out + (size_t)row0 * DM + j * 80) + q;
  uint32_t* o1 = o0 + 8 * (DM / 2);
  float s0 = 0.f, t0 = 0.f, s1 = 0.f, t1 = 0.f;
#pragma unroll
  for (int b = 0; b < 10; b++) {
    float bl = 0.f, bh = 0.f;
    if (BIAS) { const uint32_t bb = __ldg((const uint32_t*)(bias + j * 80) + b * 4 + q); bl = bf_lo(bb); bh = bf_hi(bb); }
    const uint32_t p0 = pack_bf16(acc[4 * b] + bl + bf_lo(res[2 * b]), acc[4 * b + 1] + bh + bf_hi(res[2 * b]));
    const uint32_t p1 = pack_bf16(acc[4 * b + 2] + bl + bf_lo(res[2 * b + 1]), acc[4 * b + 3] + bh + bf_hi(res[2 * b + 1]));
    o0[b * 4] = p0; o1[b * 4] = p1;
    const float a = bf_lo(p0), c = bf_hi(p0), d = bf_lo(p1), e = bf_hi(p1);
    s0 += a + c; t0 = fmaf(a, a, fmaf(c, c, t0));
    s1 += d + e; t1 = fmaf(d, d, fmaf(e, e, t1));
  }
#pragma unroll
  for (int m = 1; m < 4; m <<= 1) {
    s0 += __shfl_xor_sync(0xffffffffu, s0, m); t0 += __shfl_xor_sync(0xffffffffu, t0, m);
    s1 += __shfl_xor_sync(0xffffffffu, s1, m); t1 += __shfl_xor_sync(0xffffffffu, t1, m);
  }
  if (q == 0) st[row0 * 8 + j] = make_float2(s0, t0);
  if (q == 1) st[(row0 + 8) * 8 + j] = make_float2(s1, t1);
}
__device__ __forceinline__ void load_resid(uint32_t (&res)[20], const bf16* x, int row0, int j, int lane) {
  const uint32_t* r0 = (const uint32_t*)(x + (size_t)row0 * DM + j * 80) + (lane & 3);
#pragma unroll
  for (int b = 0; b < 10; b++) { res[2 * b] = __ldcg(r0 + b * 4); res[2 * b + 1] = __ldcg(r0 + 8 * (DM / 2) + b * 4); }
}
__device__ __forceinline__ float gelu_tanh(float t) {
  const float z = t * fmaf(t * t, 0.044715f * 0.7978845608028654f, 0.7978845608028654f);
  float th;
  asm("tanh.approx.f32 %0, %1;" : "=f"(th) : "f"(z));
  const float ht = 0.5f * t;
  return fmaf(ht, th, ht);
}
template <bool DOUBLE> __device__ __forceinline__ float2 row_coef(float s, float t) {
  const float mean = s * (1.f / DM);
  const float var = fmaxf(fmaf(-mean, mean, t * (1.f / DM)), 0.f);
  float r = rsqrtf(var + LN_EPS);
  if (DOUBLE) r *= rsqrtf(var * r * r + LN_EPS);
  return make_float2(r, -r * mean);
}
template <int N> __device__ __forceinline__ void reduce_colsum(const float* part, int ld, float* dst, int lane) {
  for (int c = lane * 4; c < N; c += 128) {
    float4 a = make_float4(0.f, 0.f, 0.f, 0.f);
#pragma unroll 8
    for (int p = 0; p < 32; p++) { const float4 v = __ldcg((const float4*)(part + p * ld + c)); a.x += v.x; a.y += v.y; a.z += v.z; a.w += v.w; }
    *(float4*)(dst + c) = a;
  }
}
template <bool DOUBLE> __device__ __forceinline__ void reduce_stats(const float2* st, float2* dst, int i, int lane) {
#pragma unroll
  for (int rr = 0; rr < 4; rr++) {
    const int r = rr * 32 + lane;
    const float4* p = (const float4*)(st + (size_t)(i * 128 + r) * 8);
    float s = 0.f, t = 0.f;
#pragma unroll
    for (int k = 0; k < 4; k++) { const float4 v = __ldcg(p + k); s += v.x + v.z; t += v.y + v.w; }
    dst[r] = row_coef<DOUBLE>(s, t);
  }
}

template <int PH, bool FIRST>
__global__ void __launch_bounds__(CHAIN_THREADS, 1) chain_kernel(const __grid_constant__ ChainParams p) {
  extern __shared__ __align__(1024) uint8_t smem[];
  const uint32_t sbase = smem_u32(smem), bars = sbase + SM_BAR;
  const uint32_t auxbar = bars + (2 * SA + 2 * SB) * 8;
  float* cs = (float*)(smem + SM_CS);
  float* sb1 = (float*)(smem + SM_B1);
  float2* srow = (float2*)(smem + SM_ROW);
  const int tid = threadIdx.x, lane = tid & 31, warp = __shfl_sync(0xffffffffu, tid >> 5, 0);
  const int i = blockIdx.x >> 3, j = blockIdx.x & 7;
  unsigned int* fl = p.flags;
  if (tid == 0) {
    for (int s = 0; s < SA; s++) { mbar_init(bars + s * 8, 1); mbar_init(bars + (SA + s) * 8, 8); }
    for (int s = 0; s < SB; s++) { mbar_init(bars + (2 * SA + s) * 8, 1); mbar_init(bars + (2 * SA + SB + s) * 8, 8); }
    mbar_init(auxbar, 32); mbar_init(auxbar + 8, 32);
    asm volatile("fence.mbarrier_init.release.cluster;" ::: "memory");
  }
  __syncthreads();
  pdl_launch();

  if (warp == 9) {
    if (lane == 0) {
      Ring r{0, 0};
      if (PH & PH_WO) produce_b<10, 2, 2>(&p.b_wo, sbase + SM_B, bars, j, r);
      if (PH & PH_W1) produce_b<10, 1, 4>(&p.b_w1, sbase + SM_B, bars, j, r);
      if (PH & PH_W2) produce_b<27, 2, 2>(&p.b_w2, sbase + SM_B, bars, j, r);
      if (PH & PH_QKV) produce_b<10, 1, 4>(&p.b_wqkv, sbase + SM_B, bars, j, r);
    }
  } else if (warp == 8) {
    if (lane == 0) {
      Ring r{0, 0};
      if (!FIRST) pdl_wait();
      if (PH & PH_WO) produce_a<10>(&p.a_o, sbase, bars, i, r);
      if (PH & PH_W1) { if (PH & PH_WO) { flag_wait(fl + i, 8); fence_async_global(); } produce_a<10>(&p.a_x1, sbase, bars, i, r); }
      if (PH & PH_W2) { if (PH & PH_W1) { flag_wait(fl + 16 + i, 8); fence_async_global(); } produce_a<27>(&p.a_h, sbase, bars, i, r); }
      if (PH & PH_QKV) { if (PH & PH_W2) { flag_wait(fl + 32 + i, 8); fence_async_global(); } produce_a<10>(&p.a_xq, sbase, bars, i, r); }
    }
  } else if (warp == 10) {
    if (!FIRST && !(PH & PH_WO)) pdl_wait();
    if (PH & PH_W1) {
      reduce_colsum<216>(g_csp_w1 + j * 216, FF, cs, lane);
      for (int c = lane; c < 216; c += 32) sb1[c] = __bfloat162float(p.b1[j * 216 + c]);
      if (PH & PH_WO) { pdl_wait(); if (lane == 0) flag_wait(fl + i, 8); __syncwarp(); }
      reduce_stats<true>(g_st1, srow, i, lane);
      mbar_arrive(auxbar);
    }
    if (PH & PH_QKV) {
      if (FIRST) {
        if (lane == 0) { flag_wait(fl + i, 8); flag_wait(fl + 16 + j, 16); }
        __syncwarp();
#pragma unroll
        for (int rr = 0; rr < 4; rr++) { const float2 v = __ldcg(&g_st0[i * 128 + rr * 32 + lane]); srow[rr * 32 + lane] = row_coef<false>(v.x, v.y); }
      } else {
        if (PH & PH_W2) { if (lane == 0) flag_wait(fl + 32 + i, 8); __syncwarp(); }
        reduce_stats<false>(g_st2, srow, i, lane);
      }
      reduce_colsum<240>(g_csp_qkv + j * 240, 1920, cs, lane);
      mbar_arrive(auxbar + 8);
    }
  } else {
    const int wg = warp >> 2, q = lane & 3;
    const int rl = wg * 64 + (warp & 3) * 16 + (lane >> 2);
    const int row0 = i * 128 + rl;
    Ring ra{0, 0}, rb{0, 0};
    if (FIRST) {
      float s[2] = {0.f, 0.f}, t[2] = {0.f, 0.f};
      uint2 xv[2][5];
#pragma unroll
      for (int rr = 0; rr < 2; rr++)
#pragma unroll
        for (int k = 0; k < 5; k++) xv[rr][k] = __ldg((const uint2*)(p.xres + (size_t)(i * 128 + j * 16 + warp * 2 + rr) * DM) + k * 32 + lane);
      uint32_t wa[20], wb[20];
      const int slab = i * 2 + (tid >= 128), tp = tid & 127;
#pragma unroll
      for (int k = 0; k < 20; k++) {
        wa[k] = tp < 120 ? __ldg((const uint32_t*)(p.wqkv + (size_t)(slab * 20 + k) * 1920 + j * 240) + tp) : 0u;
        wb[k] = tp < 108 ? __ldg((const uint32_t*)(p.w1 + (size_t)(slab * 20 + k) * FF + j * 216) + tp) : 0u;
      }
#pragma unroll
      for (int rr = 0; rr < 2; rr++) {
#pragma unroll
        for (int k = 0; k < 5; k++) {
          const float a = bf_lo(xv[rr][k].x), b = bf_hi(xv[rr][k].x), c = bf_lo(xv[rr][k].y), d = bf_hi(xv[rr][k].y);
          s[rr] += (a + b) + (c + d);
          t[rr] = fmaf(a, a, fmaf(b, b, fmaf(c, c, fmaf(d, d, t[rr]))));
        }
#pragma unroll
        for (int m = 1; m < 32; m <<= 1) { s[rr] += __shfl_xor_sync(0xffffffffu, s[rr], m); t[rr] += __shfl_xor_sync(0xffffffffu, t[rr], m); }
        if (lane == 0) g_st0[i * 128 + j * 16 + warp * 2 + rr] = make_float2(s[rr], t[rr]);
      }
      float a0 = 0.f, a1 = 0.f, b0 = 0.f, b1 = 0.f;
#pragma unroll
      for (int k = 0; k < 20; k++) { a0 += bf_lo(wa[k]); a1 += bf_hi(wa[k]); b0 += bf_lo(wb[k]); b1 += bf_hi(wb[k]); }
      if (tp < 120) *(float2*)(g_csp_qkv + slab * 1920 + j * 240 + tp * 2) = make_float2(a0, a1);
      if (tp < 108) *(float2*)(g_csp_w1 + slab * FF + j * 216 + tp * 2) = make_float2(b0, b1);
      named_bar(1, 256);
      if (tid == 0) { flag_signal(fl + i); flag_signal(fl + 16 + j); }
    }
    if (PH & PH_WO) {
      uint32_t res[20];
      load_resid(res, p.xres, row0, j, lane);
      float acc[40];
      mainloop<80, 10, 2, 2>(acc, sbase, bars, wg, lane, ra, rb);
      pdl_wait();
      epi_resid<false>(acc, res, nullptr, g_x1, g_st1, row0, j, lane);
      if (PH & PH_W1) { fence_async_global(); named_bar(1, 256); if (tid == 0) flag_signal(fl + i); }
    }
    if (PH & PH_W1) {
      float acc[108];
      mainloop<216, 10, 1, 4>(acc, sbase, bars, wg, lane, ra, rb);
      if (!(PH & PH_WO)) pdl_wait();
      mbar_wait(auxbar, 0);
      const float2 c0 = srow[rl], c1 = srow[rl + 8];
      uint32_t* o0 = (uint32_t*)(g_h + (size_t)row0 * FF + j * 216) + q;
      uint32_t* o1 = o0 + 8 * (FF / 2);
#pragma unroll
      for (int b = 0; b < 27; b++) {
        const float2 cc = *(const float2*)(cs + b * 8 + q * 2), bb = *(const float2*)(sb1 + b * 8 + q * 2);
        o0[b * 4] = pack_bf16(gelu_tanh(fmaf(c0.x, acc[4 * b], fmaf(c0.y, cc.x, bb.x))), gelu_tanh(fmaf(c0.x, acc[4 * b + 1], fmaf(c0.y, cc.y, bb.y))));
        o1[b * 4] = pack_bf16(gelu_tanh(fmaf(c1.x, acc[4 * b + 2], fmaf(c1.y, cc.x, bb.x))), gelu_tanh(fmaf(c1.x, acc[4 * b + 3], fmaf(c1.y, cc.y, bb.y))));
      }
      if (PH & PH_W2) { fence_async_global(); named_bar(1, 256); if (tid == 0) flag_signal(fl + 16 + i); }
    }
    if (PH & PH_W2) {
      if (!(PH & (PH_WO | PH_W1))) pdl_wait();
      uint32_t res[20];
      load_resid(res, g_x1, row0, j, lane);
      float acc[40];
      mainloop<80, 27, 2, 2>(acc, sbase, bars, wg, lane, ra, rb);
      epi_resid<true>(acc, res, p.b2, p.x2out, g_st2, row0, j, lane);
      if (PH & PH_QKV) { fence_async_global(); named_bar(1, 256); if (tid == 0) flag_signal(fl + 32 + i); }
    }
    if (PH & PH_QKV) {
      float acc[120];
      mainloop<240, 10, 1, 4>(acc, sbase, bars, wg, lane, ra, rb);
      if (PH == PH_QKV) pdl_wait();
      mbar_wait(auxbar + 8, 0);
      const float2 c0 = srow[rl], c1 = srow[rl + 8];
      const bool mu0 = is_mufu(row0 >> 3), mu1 = is_mufu((row0 >> 3) + 1);
      const float QS = 0.22360679774997896f * 1.4426950408889634f;
      const float ks0 = mu0 ? 1.f : 0x1p-22f, ks1 = mu1 ? 1.f : 0x1p-22f;
      uint8_t* base = (uint8_t*)g_qkv + (size_t)(j * 12) * HEAD_BYTES + (row0 >> 3) * 384 + (row0 & 7) * 16;
#pragma unroll
      for (int b = 0; b < 30; b++) {
        const int c = (b % 5) * 8 + q * 2;
        const int hh = c >= 20, d = c - hh * 20;
        const int hl = (b / 5) * 2 + hh, hs = j * 12 + hl;
        const float s0 = hs < 32 ? QS : (hs < 64 ? ks0 : 1.f), s1 = hs < 32 ? QS : (hs < 64 ? ks1 : 1.f);
        const float2 cc = *(const float2*)(cs + b * 8 + q * 2);
        uint8_t* ptr = base + hl * HEAD_BYTES + (d >> 3) * 128 + (d & 7) * 2;
        *(uint32_t*)ptr = pack_bf16(fmaf(c0.x, acc[4 * b], c0.y * cc.x) * s0, fmaf(c0.x, acc[4 * b + 1], c0.y * cc.y) * s0);
        *(uint32_t*)(ptr + 384) = pack_bf16(fmaf(c1.x, acc[4 * b + 2], c1.y * cc.x) * s1, fmaf(c1.x, acc[4 * b + 3], c1.y * cc.y) * s1);
        if ((b % 5 == 2 || b % 5 == 4) && d == 18) {
          const uint2 eq = make_uint2(0x3F803F80u, 0x00003F80u), ek = make_uint2(0x377C3C00u, 0x00003020u), ev = make_uint2(0x00003F80u, 0u), z = make_uint2(0u, 0u);
          *(uint2*)(ptr + 4) = hs < 32 ? eq : (hs < 64 ? (mu0 ? z : ek) : ev);
          *(uint2*)(ptr + 4 + 384) = hs < 32 ? eq : (hs < 64 ? (mu1 ? z : ek) : ev);
        }
      }
    }
  }
}

__device__ __forceinline__ uint32_t exp2_poly_pair(float a0, float a1) {
  const uint32_t v = __byte_perm(__float_as_uint(a0), __float_as_uint(a1), 0x7430);
  const uint32_t e = __byte_perm(__float_as_uint(a0), __float_as_uint(a1), 0x6521);
  uint32_t u;
  asm("fma.rn.f16x2 %0, %1, %2, %3;" : "=r"(u) : "r"(v), "r"(0x1d611d61u), "r"(0xa012a012u));
  asm("fma.rn.f16x2 %0, %1, %2, %3;" : "=r"(u) : "r"(u), "r"(v), "r"(0x21622162u));
  return e * 128u + u;
}
constexpr int ATT_SMEM = 2 * HEAD_BYTES + 256;

__device__ __forceinline__ void att_store(const float (&O)[12], int row0, int h, int lane) {
  const float l0 = __shfl_sync(0xffffffffu, O[8], (lane & ~3) | 2), l1 = __shfl_sync(0xffffffffu, O[10], (lane & ~3) | 2);
  const float r0 = __fdividef(1.f, l0), r1 = __fdividef(1.f, l1);
  uint32_t* o0 = (uint32_t*)(g_o + (size_t)row0 * DM + h * 20) + (lane & 3);
  uint32_t* o1 = o0 + 8 * (DM / 2);
#pragma unroll
  for (int c = 0; c < 3; c++)
    if (c < 2 || (lane & 3) < 2) {
      o0[4 * c] = pack_bf16(O[4 * c] * r0, O[4 * c + 1] * r0);
      o1[4 * c] = pack_bf16(O[4 * c + 2] * r1, O[4 * c + 3] * r1);
    }
}

__global__ void __launch_bounds__(512, 1) att_kernel(unsigned int* reset_a, unsigned int* reset_b, const bf16* pf0, const bf16* pf1, const uint32_t* zeros) {
  extern __shared__ __align__(1024) uint8_t smem[];
  const uint32_t sK = smem_u32(smem), sV = sK + HEAD_BYTES, bars = sV + HEAD_BYTES + 128;
  float* red = (float*)(smem + 2 * HEAD_BYTES + 192);
  const int h = blockIdx.x >> 2, qt = blockIdx.x & 3;
  const int tid = threadIdx.x, lane = tid & 31, wg = __shfl_sync(0xffffffffu, tid >> 7, 0), warp = (tid >> 5) & 3;
  if (tid == 0) {
    for (int c = 0; c < 8; c++) mbar_init(bars + c * 8, 1);
    asm volatile("fence.mbarrier_init.release.cluster;" ::: "memory");
    if (pf0) {
      prefetch_l2((const uint8_t*)pf0 + blockIdx.x * 6400, 6400);
      prefetch_l2((const uint8_t*)pf1 + blockIdx.x * 17280, 17280);
    }
  }
  const uint32_t z0 = __ldg(zeros + (tid & 1)), z1 = __ldg(zeros + 2 + (tid & 1));
  __syncthreads();
  pdl_wait();
  pdl_launch();
  const uint8_t* gq = (const uint8_t*)g_qkv + (size_t)h * HEAD_BYTES;
  if (tid == 0) {
    for (int c = 0; c < 8; c++) {
      const int k0 = c == 0 ? 0 : c * 12288 + 128, k1 = c == 7 ? HEAD_BYTES : (c + 1) * 12288 + 128;
      mbar_expect_tx(bars + c * 8, 12288 + (k1 - k0));
      bulk_g2s(sK + k0, gq + 32 * HEAD_BYTES + k0, k1 - k0, bars + c * 8);
      bulk_g2s(sV + c * 12288, gq + 64 * HEAD_BYTES + c * 12288, 12288, bars + c * 8);
    }
  }
  if (blockIdx.x == 0 && tid < 64) { reset_a[tid] = 0u; if (reset_b) reset_b[tid] = 0u; }
  const uint64_t dK = mk_desc(sK, 128, 384, 0);
  const uint64_t dV = mk_desc(sV, 384, 128, 0);
  float qn = 0.f;
  bool bad = false;
#pragma unroll 1
  for (int tt = 0; tt < 2; tt++) {
    const int row0 = qt * 512 + (tt * 4 + wg) * 64 + warp * 16 + (lane >> 2);
    uint32_t q[6];
    {
      const uint32_t* qa = (const uint32_t*)(gq + (row0 >> 3) * 384 + (row0 & 7) * 16) + (lane & 3);
      q[0] = __ldcg(qa); q[1] = __ldcg(qa + 96); q[2] = __ldcg(qa + 32); q[3] = __ldcg(qa + 128); q[4] = __ldcg(qa + 64); q[5] = __ldcg(qa + 160);
    }
    float S[64], O[12];
    uint32_t P[32];
#pragma unroll
    for (int k = 0; k < 12; k++) O[k] = 0.f;
#pragma unroll
    for (int k = 0; k < 64; k++) S[k] = 0.f;
    uint64_t gk = dK, gv = dV;
#pragma unroll 1
    for (int g = 0; g < 16; g++) {
      if ((g & 1) == 0) mbar_wait(bars + (g >> 1) * 8, 0);
      wg_fence();
      wgmma_rs_n128<0>(S, q[0], q[1], q[2], q[3], gk, 0);
      wgmma_rs_n128<0>(S, q[4], q[5], z0, z1, gk + 16, 1);
      wg_commit();
      wg_wait<0>();
      fence_regs(S);
#pragma unroll
      for (int b = 0; b < 16; b++) {
        if (is_mufu(b)) { P[2 * b] = pack_bf16(ex2(S[4 * b]), ex2(S[4 * b + 1])); P[2 * b + 1] = pack_bf16(ex2(S[4 * b + 2]), ex2(S[4 * b + 3])); }
        else { P[2 * b] = exp2_poly_pair(S[4 * b], S[4 * b + 1]); P[2 * b + 1] = exp2_poly_pair(S[4 * b + 2], S[4 * b + 3]); }
      }
      fence_regs(P);
      wg_fence();
#pragma unroll
      for (int s = 0; s < 8; s++) wgmma_rs_n24<1>(O, P[4 * s], P[4 * s + 1], P[4 * s + 2], P[4 * s + 3], gv + s * 48, 1);
      wg_commit();
      wg_wait<0>();
      gk += 384; gv += 384;
    }
    fence_regs(O);
    att_store(O, row0, h, lane);
    {
      const uint32_t x4 = (lane & 3) < 2 ? q[4] : 0u, x5 = (lane & 3) < 2 ? q[5] : 0u;
      float n0 = bf_lo(q[0]) * bf_lo(q[0]) + bf_hi(q[0]) * bf_hi(q[0]) + bf_lo(q[2]) * bf_lo(q[2]) + bf_hi(q[2]) * bf_hi(q[2]) + bf_lo(x4) * bf_lo(x4) + bf_hi(x4) * bf_hi(x4);
      float n1 = bf_lo(q[1]) * bf_lo(q[1]) + bf_hi(q[1]) * bf_hi(q[1]) + bf_lo(q[3]) * bf_lo(q[3]) + bf_hi(q[3]) * bf_hi(q[3]) + bf_lo(x5) * bf_lo(x5) + bf_hi(x5) * bf_hi(x5);
      n0 += __shfl_xor_sync(0xffffffffu, n0, 1); n1 += __shfl_xor_sync(0xffffffffu, n1, 1);
      n0 += __shfl_xor_sync(0xffffffffu, n0, 2); n1 += __shfl_xor_sync(0xffffffffu, n1, 2);
      bad |= !(n0 <= 3e38f) || !(n1 <= 3e38f);
      qn = fmaxf(qn, fmaxf(n0, n1));
      float m = 0.f;
#pragma unroll
      for (int k = 0; k < 12; k++) { m = fmaxf(m, fabsf(O[k])); bad |= (O[k] != O[k]); }
      bad |= !(m <= 3e38f);
      if ((lane & 3) == 2) bad |= !(O[8] >= 0x1p-20f) || !(O[10] >= 0x1p-20f);
    }
  }
  float kn = 0.f;
  bool knan = false;
#pragma unroll
  for (int kq = 0; kq < 4; kq++) {
    const int key = kq * 512 + tid;
    const uint8_t* kp = smem + (key >> 3) * 384 + (key & 7) * 16;
    const uint4 a = *(const uint4*)kp, b = *(const uint4*)(kp + 128);
    const uint2 c = *(const uint2*)(kp + 256);
    const uint32_t w[10] = {a.x, a.y, a.z, a.w, b.x, b.y, b.z, b.w, c.x, c.y};
    float n = 0.f;
#pragma unroll
    for (int k = 0; k < 10; k++) n = fmaf(bf_lo(w[k]), bf_lo(w[k]), fmaf(bf_hi(w[k]), bf_hi(w[k]), n));
    n *= is_mufu(key >> 3) ? 1.f : 0x1p44f;
    knan |= !(n <= 3e38f);
    kn = fmaxf(kn, n);
  }
  if (knan) kn = 3e38f;
  kn = __uint_as_float(__reduce_max_sync(0xffffffffu, __float_as_uint(kn)));
  if (lane == 0) red[tid >> 5] = kn;
  __syncthreads();
#pragma unroll
  for (int k = 0; k < 16; k++) kn = fmaxf(kn, red[k]);
  bad |= !(qn * kn <= 3600.f);
  if (__syncthreads_or(bad)) {
#pragma unroll 1
    for (int tt = 0; tt < 2; tt++) {
      const int row0 = qt * 512 + (tt * 4 + wg) * 64 + warp * 16 + (lane >> 2);
      uint32_t q[6];
      const uint32_t* qa = (const uint32_t*)(gq + (row0 >> 3) * 384 + (row0 & 7) * 16) + (lane & 3);
      q[0] = __ldcg(qa); q[1] = __ldcg(qa + 96); q[2] = __ldcg(qa + 32); q[3] = __ldcg(qa + 128); q[4] = __ldcg(qa + 64); q[5] = __ldcg(qa + 160);
      if ((lane & 3) >= 2) { q[4] = 0u; q[5] = 0u; }
      float S[64], O[12], m0 = -INFINITY, m1 = -INFINITY;
      uint32_t P[32];
#pragma unroll
      for (int k = 0; k < 12; k++) O[k] = 0.f;
#pragma unroll
      for (int k = 0; k < 64; k++) S[k] = 0.f;
      uint64_t gk = dK, gv = dV;
#pragma unroll 1
      for (int g = 0; g < 16; g++) {
        wg_fence();
        wgmma_rs_n128<0>(S, q[0], q[1], q[2], q[3], gk, 0);
        wgmma_rs_n128<0>(S, q[4], q[5], z0, z1, gk + 16, 1);
        wg_commit();
        wg_wait<0>();
        fence_regs(S);
        float x0 = m0, x1 = m1;
#pragma unroll
        for (int b = 0; b < 16; b++) {
          if (!is_mufu(b)) { S[4 * b] *= 0x1p22f; S[4 * b + 1] *= 0x1p22f; S[4 * b + 2] *= 0x1p22f; S[4 * b + 3] *= 0x1p22f; }
          x0 = fmaxf(x0, fmaxf(S[4 * b], S[4 * b + 1]));
          x1 = fmaxf(x1, fmaxf(S[4 * b + 2], S[4 * b + 3]));
        }
        x0 = fmaxf(x0, __shfl_xor_sync(0xffffffffu, x0, 1)); x1 = fmaxf(x1, __shfl_xor_sync(0xffffffffu, x1, 1));
        x0 = fmaxf(x0, __shfl_xor_sync(0xffffffffu, x0, 2)); x1 = fmaxf(x1, __shfl_xor_sync(0xffffffffu, x1, 2));
        const float al0 = ex2(m0 - x0), al1 = ex2(m1 - x1);
        m0 = x0; m1 = x1;
#pragma unroll
        for (int c = 0; c < 3; c++) { O[4 * c] *= al0; O[4 * c + 1] *= al0; O[4 * c + 2] *= al1; O[4 * c + 3] *= al1; }
#pragma unroll
        for (int b = 0; b < 16; b++) {
          P[2 * b] = pack_bf16(ex2(S[4 * b] - m0), ex2(S[4 * b + 1] - m0));
          P[2 * b + 1] = pack_bf16(ex2(S[4 * b + 2] - m1), ex2(S[4 * b + 3] - m1));
        }
        fence_regs(P);
        fence_regs(O);
        wg_fence();
#pragma unroll
        for (int s = 0; s < 8; s++) wgmma_rs_n24<1>(O, P[4 * s], P[4 * s + 1], P[4 * s + 2], P[4 * s + 3], gv + s * 48, 1);
        wg_commit();
        wg_wait<0>();
        fence_regs(O);
        gk += 384; gv += 384;
      }
      att_store(O, row0, h, lane);
    }
  }
}

__device__ uint32_t g_zeros[4];

typedef CUresult (*EncodeFn)(CUtensorMap*, CUtensorMapDataType, cuuint32_t, void*, const cuuint64_t*, const cuuint64_t*, const cuuint32_t*,
                             const cuuint32_t*, CUtensorMapInterleave, CUtensorMapSwizzle, CUtensorMapL2promotion, CUtensorMapFloatOOBfill);

static void make_a(EncodeFn enc, CUtensorMap* m, const void* ptr, int K) {
  cuuint64_t dims[2] = {(cuuint64_t)K, (cuuint64_t)SEQ}, strides[1] = {(cuuint64_t)K * 2};
  cuuint32_t box[2] = {64, 128}, es[2] = {1, 1};
  enc(m, CU_TENSOR_MAP_DATA_TYPE_BFLOAT16, 2, (void*)ptr, dims, strides, box, es, CU_TENSOR_MAP_INTERLEAVE_NONE, CU_TENSOR_MAP_SWIZZLE_128B,
      CU_TENSOR_MAP_L2_PROMOTION_L2_128B, CU_TENSOR_MAP_FLOAT_OOB_FILL_NONE);
}
static void make_b(EncodeFn enc, CUtensorMap* m, const void* ptr, int K, int N, int BN) {
  cuuint64_t dims[3] = {(cuuint64_t)BN, (cuuint64_t)(N / BN), (cuuint64_t)K}, strides[2] = {(cuuint64_t)BN * 2, (cuuint64_t)N * 2};
  cuuint32_t box[3] = {64, 1, 64}, es[3] = {1, 1, 1};
  enc(m, CU_TENSOR_MAP_DATA_TYPE_BFLOAT16, 3, (void*)ptr, dims, strides, box, es, CU_TENSOR_MAP_INTERLEAVE_NONE, CU_TENSOR_MAP_SWIZZLE_128B,
      CU_TENSOR_MAP_L2_PROMOTION_L2_128B, CU_TENSOR_MAP_FLOAT_OOB_FILL_NONE);
}
template <typename... KArgs, typename... Args>
static void launch(void (*kern)(KArgs...), int threads, int smem, bool pdl, Args... args) {
  cudaFuncSetAttribute(kern, cudaFuncAttributeMaxDynamicSharedMemorySize, smem);
  cudaLaunchConfig_t cfg = {};
  cfg.gridDim = dim3(128); cfg.blockDim = dim3(threads); cfg.dynamicSmemBytes = smem; cfg.stream = cudaStreamPerThread;
  cudaLaunchAttribute at[1];
  at[0].id = cudaLaunchAttributeProgrammaticStreamSerialization; at[0].val.programmaticStreamSerializationAllowed = 1;
  cfg.attrs = at; cfg.numAttrs = pdl ? 1 : 0;
  cudaLaunchKernelEx(&cfg, kern, KArgs(args)...);
}

extern "C" void kernel_launch(void* const* d_in, const int* in_sizes, int n_in, void* d_out, int out_size) {
  const bf16* x = (const bf16*)d_in[0];
  const bf16* wqkv = (const bf16*)d_in[1];
  const bf16* wo = (const bf16*)d_in[2];
  const bf16* w1 = (const bf16*)d_in[4];
  const bf16* b1 = (const bf16*)d_in[5];
  const bf16* w2 = (const bf16*)d_in[6];
  const bf16* b2 = (const bf16*)d_in[7];
  void* fn = nullptr;
  cudaDriverEntryPointQueryResult qr;
  cudaGetDriverEntryPoint("cuTensorMapEncodeTiled", &fn, cudaEnableDefault, &qr);
  EncodeFn enc = (EncodeFn)fn;
  void *po, *px1, *px2, *ph, *pf, *pz;
  cudaGetSymbolAddress(&po, g_o); cudaGetSymbolAddress(&px1, g_x1); cudaGetSymbolAddress(&px2, g_x2);
  cudaGetSymbolAddress(&ph, g_h); cudaGetSymbolAddress(&pf, g_flags); cudaGetSymbolAddress(&pz, g_zeros);
  unsigned int* flags = (unsigned int*)pf;

  ChainParams p;
  make_a(enc, &p.a_o, po, DM); make_a(enc, &p.a_x1, px1, DM); make_a(enc, &p.a_h, ph, FF); make_a(enc, &p.a_xq, x, DM);
  make_b(enc, &p.b_wo, wo, DM, DM, 80); make_b(enc, &p.b_w1, w1, DM, FF, 216); make_b(enc, &p.b_w2, w2, FF, DM, 80);
  make_b(enc, &p.b_wqkv, wqkv, DM, 1920, 240);
  p.xres = x; p.x2out = (bf16*)px2; p.b1 = b1; p.b2 = b2; p.wqkv = wqkv; p.w1 = w1; p.flags = flags;

  launch(chain_kernel<PH_QKV, true>, CHAIN_THREADS, CHAIN_SMEM, false, p);
  launch(att_kernel, 512, ATT_SMEM, true, flags, flags + 128, wo, w2, (const uint32_t*)pz);
  make_a(enc, &p.a_xq, px2, DM);
  p.flags = flags + 64;
  launch(chain_kernel<PH_WO | PH_W1 | PH_W2 | PH_QKV, false>, CHAIN_THREADS, CHAIN_SMEM, true, p);
  launch(att_kernel, 512, ATT_SMEM, true, flags + 64, (unsigned int*)nullptr, (const bf16*)nullptr, (const bf16*)nullptr, (const uint32_t*)pz);
  p.xres = (const bf16*)px2; p.x2out = (bf16*)d_out; p.flags = flags + 128;
  launch(chain_kernel<PH_WO | PH_W1 | PH_W2, false>, CHAIN_THREADS, CHAIN_SMEM, true, p);
}
```

```cpp
#include <cuda_runtime.h>
#include <cuda_bf16.h>
#include <cuda.h>
#include <stdint.h>

#define GATE 0
typedef __nv_bfloat16 bf16;

constexpr int SEQ = 2048, DM = 640, FF = 1728;
constexpr float LN_EPS = 1e-5f;
constexpr int HEAD_BYTES = 98304;
constexpr uint32_t MUFU_MASK = 0x4949u;
__host__ __device__ constexpr bool is_mufu(int g) { return (MUFU_MASK >> (g & 15)) & 1u; }

__device__ __align__(1024) bf16 g_qkv[96 * (HEAD_BYTES / 2)];
constexpr int WT_WO = 0, WT_W1 = WT_WO + 40 * 20480, WT_W2 = WT_W1 + 80 * 28672, WT_QKV = WT_W2 + 72 * 30720, WT_END = WT_QKV + 80 * 32768;
__device__ __align__(1024) uint8_t g_wt[WT_END];
__device__ __forceinline__ int x_line(int row, int cg) { return (((row >> 7) * 10 + (cg >> 3)) * 16 + ((row >> 3) & 15)) * 8 + (cg & 7); }
__device__ __forceinline__ int o_line(int row, int cg) { return (((row >> 6) * 10 + (cg >> 3)) * 8 + ((row >> 3) & 7)) * 8 + (cg & 7); }
__device__ __forceinline__ int h_line(int row, int cg) { return (((row >> 6) * 18 + cg / 12) * 8 + ((row >> 3) & 7)) * 12 + cg % 12; }
__device__ __align__(1024) bf16 g_x0[SEQ * DM];
__device__ __align__(1024) bf16 g_o[SEQ * DM];
__device__ __align__(1024) bf16 g_x1[SEQ * DM];
__device__ __align__(1024) bf16 g_x2[SEQ * DM];
__device__ __align__(1024) bf16 g_h[SEQ * FF];
constexpr int FLAG_SET = 320, NORM_OFF = 256;
struct Small {
  float2 st0[4 * SEQ];
  float2 st1[8 * SEQ];
  float2 st2[8 * SEQ];
  float csp_qkv[16 * 1920];
  float csp_w1[10 * FF];
  float cs_qkv[1920];
  unsigned int flags[3 * FLAG_SET];
  uint32_t zeros[4];
};
__device__ __align__(1024) Small g_s;

#define TS(k, s) do {} while (0)
__device__ __forceinline__ uint32_t smem_u32(const void* p) { return (uint32_t)__cvta_generic_to_shared(p); }
__device__ __forceinline__ void mbar_init(uint32_t bar, int cnt) { asm volatile("mbarrier.init.shared::cta.b64 [%0], %1;" ::"r"(bar), "r"(cnt) : "memory"); }
__device__ __forceinline__ void mbar_expect_tx(uint32_t bar, uint32_t bytes) { asm volatile("mbarrier.arrive.expect_tx.shared::cta.b64 _, [%0], %1;" ::"r"(bar), "r"(bytes) : "memory"); }
__device__ __forceinline__ void mbar_arrive(uint32_t bar) { asm volatile("mbarrier.arrive.shared::cta.b64 _, [%0];" ::"r"(bar) : "memory"); }
__device__ __forceinline__ bool mbar_try(uint32_t bar, uint32_t parity) {
  uint32_t ok;
  asm volatile("{\n.reg .pred p;\nmbarrier.try_wait.parity.shared::cta.b64 p, [%1], %2;\nselp.u32 %0, 1, 0, p;\n}\n" : "=r"(ok) : "r"(bar), "r"(parity) : "memory");
  return ok != 0;
}
__device__ __forceinline__ void mbar_wait(uint32_t bar, uint32_t parity) {
  if (mbar_try(bar, parity)) return;
#pragma unroll 1
  for (int it = 0; it < (1 << 22); it++)
    if (mbar_try(bar, parity)) return;
  __trap();
}
__device__ __forceinline__ void flag_wait(const unsigned int* f, unsigned int target) {
  unsigned int v;
#pragma unroll 1
  for (int it = 0; it < (1 << 22); it++) {
    asm volatile("ld.acquire.gpu.global.u32 %0, [%1];" : "=r"(v) : "l"(f) : "memory");
    if (v >= target) return;
  }
  __trap();
}
__device__ __forceinline__ void flag_signal(unsigned int* f) { asm volatile("red.release.gpu.global.add.u32 [%0], 1;" ::"l"(f) : "memory"); }
__device__ __forceinline__ void fence_async_global() { asm volatile("fence.proxy.async.global;" ::: "memory"); }
__device__ __forceinline__ void pdl_wait() { asm volatile("griddepcontrol.wait;" ::: "memory"); }
__device__ __forceinline__ void pdl_launch() { asm volatile("griddepcontrol.launch_dependents;" ::: "memory"); }
__device__ __forceinline__ void named_bar(int id, int n) { asm volatile("bar.sync %0, %1;" ::"r"(id), "r"(n) : "memory"); }
__device__ __forceinline__ void bulk_g2s(uint32_t dst, const void* src, uint32_t bytes, uint32_t bar) {
  asm volatile("cp.async.bulk.shared::cluster.global.mbarrier::complete_tx::bytes [%0], [%1], %2, [%3];" ::"r"(dst), "l"(src), "r"(bytes), "r"(bar) : "memory");
}
__device__ __forceinline__ void prefetch_l2(const void* src, uint32_t bytes) { asm volatile("cp.async.bulk.prefetch.L2.global [%0], %1;" ::"l"(src), "r"(bytes) : "memory"); }
__device__ __forceinline__ void tma_2d(uint32_t dst, const CUtensorMap* m, int c0, int c1, uint32_t bar) {
  asm volatile("cp.async.bulk.tensor.2d.shared::cluster.global.mbarrier::complete_tx::bytes [%0], [%1, {%3, %4}], [%2];" ::"r"(dst), "l"(m), "r"(bar), "r"(c0), "r"(c1) : "memory");
}
__device__ __forceinline__ void tma_3d(uint32_t dst, const CUtensorMap* m, int c0, int c1, int c2, uint32_t bar) {
  asm volatile("cp.async.bulk.tensor.3d.shared::cluster.global.mbarrier::complete_tx::bytes [%0], [%1, {%3, %4, %5}], [%2];" ::"r"(dst), "l"(m), "r"(bar), "r"(c0), "r"(c1), "r"(c2) : "memory");
}
__device__ __forceinline__ void prefetch_map(const CUtensorMap* m) { asm volatile("prefetch.tensormap [%0];" ::"l"(m) : "memory"); }
__device__ __forceinline__ void wg_fence() { asm volatile("wgmma.fence.sync.aligned;" ::: "memory"); }
__device__ __forceinline__ void wg_commit() { asm volatile("wgmma.commit_group.sync.aligned;" ::: "memory"); }
template <int N> __device__ __forceinline__ void wg_wait() { asm volatile("wgmma.wait_group.sync.aligned %0;" ::"n"(N) : "memory"); }
template <int N> __device__ __forceinline__ void fence_regs(float (&d)[N]) {
#pragma unroll
  for (int i = 0; i < N; i++) asm volatile("" : "+f"(d[i])::"memory");
}
template <int N> __device__ __forceinline__ void fence_regs(uint32_t (&d)[N]) {
#pragma unroll
  for (int i = 0; i < N; i++) asm volatile("" : "+r"(d[i])::"memory");
}
__device__ __forceinline__ uint64_t mk_desc(uint32_t addr, uint32_t lbo, uint32_t sbo, uint64_t swz) {
  return (uint64_t)((addr & 0x3FFFF) >> 4) | ((uint64_t)(lbo >> 4) << 16) | ((uint64_t)(sbo >> 4) << 32) | (swz << 62);
}
__device__ __forceinline__ uint32_t pack_bf16(float lo, float hi) {
  uint32_t r;
  asm("cvt.rn.bf16x2.f32 %0, %1, %2;" : "=r"(r) : "f"(hi), "f"(lo));
  return r;
}
__device__ __forceinline__ float bf_lo(uint32_t v) { return __uint_as_float(v << 16); }
__device__ __forceinline__ float bf_hi(uint32_t v) { return __uint_as_float(v & 0xFFFF0000u); }
__device__ __forceinline__ float ex2(float x) { float r; asm("ex2.approx.ftz.f32 %0, %1;" : "=f"(r) : "f"(x)); return r; }

template<int TB> __device__ __forceinline__ void wgmma_rs_n24(float (&d)[12], uint32_t a0, uint32_t a1, uint32_t a2, uint32_t a3, uint64_t db, int sd) {
  asm volatile("{\n.reg .pred p;\nsetp.ne.b32 p, %17, 0;\n"
    "wgmma.mma_async.sync.aligned.m64n24k16.f32.bf16.bf16 "
    "{%0,%1,%2,%3,%4,%5,%6,%7,%8,%9,%10,%11}, "
    "{%12,%13,%14,%15}, %16, p, 1, 1, %18;\n}\n"
    : "+f"(d[0]),"+f"(d[1]),"+f"(d[2]),"+f"(d[3]),"+f"(d[4]),"+f"(d[5]),"+f"(d[6]),"+f"(d[7]),"+f"(d[8]),"+f"(d[9]),"+f"(d[10]),"+f"(d[11])
    : "r"(a0), "r"(a1), "r"(a2), "r"(a3), "l"(db), "r"(sd), "n"(TB));
}
template<int TB> __device__ __forceinline__ void wgmma_rs_n128(float (&d)[64], uint32_t a0, uint32_t a1, uint32_t a2, uint32_t a3, uint64_t db, int sd) {
  asm volatile("{\n.reg .pred p;\nsetp.ne.b32 p, %69, 0;\n"
    "wgmma.mma_async.sync.aligned.m64n128k16.f32.bf16.bf16 "
    "{%0,%1,%2,%3,%4,%5,%6,%7,%8,%9,%10,%11,%12,%13,%14,%15,%16,%17,%18,%19,%20,%21,%22,%23,%24,%25,%26,%27,%28,%29,%30,%31,%32,%33,%34,%35,%36,%37,%38,%39,%40,%41,%42,%43,%44,%45,%46,%47,%48,%49,%50,%51,%52,%53,%54,%55,%56,%57,%58,%59,%60,%61,%62,%63}, "
    "{%64,%65,%66,%67}, %68, p, 1, 1, %70;\n}\n"
    : "+f"(d[0]),"+f"(d[1]),"+f"(d[2]),"+f"(d[3]),"+f"(d[4]),"+f"(d[5]),"+f"(d[6]),"+f"(d[7]),"+f"(d[8]),"+f"(d[9]),"+f"(d[10]),"+f"(d[11]),"+f"(d[12]),"+f"(d[13]),"+f"(d[14]),"+f"(d[15]),"+f"(d[16]),"+f"(d[17]),"+f"(d[18]),"+f"(d[19]),"+f"(d[20]),"+f"(d[21]),"+f"(d[22]),"+f"(d[23]),"+f"(d[24]),"+f"(d[25]),"+f"(d[26]),"+f"(d[27]),"+f"(d[28]),"+f"(d[29]),"+f"(d[30]),"+f"(d[31]),"+f"(d[32]),"+f"(d[33]),"+f"(d[34]),"+f"(d[35]),"+f"(d[36]),"+f"(d[37]),"+f"(d[38]),"+f"(d[39]),"+f"(d[40]),"+f"(d[41]),"+f"(d[42]),"+f"(d[43]),"+f"(d[44]),"+f"(d[45]),"+f"(d[46]),"+f"(d[47]),"+f"(d[48]),"+f"(d[49]),"+f"(d[50]),"+f"(d[51]),"+f"(d[52]),"+f"(d[53]),"+f"(d[54]),"+f"(d[55]),"+f"(d[56]),"+f"(d[57]),"+f"(d[58]),"+f"(d[59]),"+f"(d[60]),"+f"(d[61]),"+f"(d[62]),"+f"(d[63])
    : "r"(a0), "r"(a1), "r"(a2), "r"(a3), "l"(db), "r"(sd), "n"(TB));
}
__device__ __forceinline__ void wgmma_ss(float (&d)[80], uint64_t da, uint64_t db, int sd) {
  asm volatile("{\n.reg .pred p;\nsetp.ne.b32 p, %82, 0;\n"
    "wgmma.mma_async.sync.aligned.m64n160k16.f32.bf16.bf16 "
    "{%0,%1,%2,%3,%4,%5,%6,%7,%8,%9,%10,%11,%12,%13,%14,%15,%16,%17,%18,%19,%20,%21,%22,%23,%24,%25,%26,%27,%28,%29,%30,%31,%32,%33,%34,%35,%36,%37,%38,%39,%40,%41,%42,%43,%44,%45,%46,%47,%48,%49,%50,%51,%52,%53,%54,%55,%56,%57,%58,%59,%60,%61,%62,%63,%64,%65,%66,%67,%68,%69,%70,%71,%72,%73,%74,%75,%76,%77,%78,%79}, "
    "%80, %81, p, 1, 1, 0, 1;\n}\n"
    : "+f"(d[0]),"+f"(d[1]),"+f"(d[2]),"+f"(d[3]),"+f"(d[4]),"+f"(d[5]),"+f"(d[6]),"+f"(d[7]),"+f"(d[8]),"+f"(d[9]),"+f"(d[10]),"+f"(d[11]),"+f"(d[12]),"+f"(d[13]),"+f"(d[14]),"+f"(d[15]),"+f"(d[16]),"+f"(d[17]),"+f"(d[18]),"+f"(d[19]),"+f"(d[20]),"+f"(d[21]),"+f"(d[22]),"+f"(d[23]),"+f"(d[24]),"+f"(d[25]),"+f"(d[26]),"+f"(d[27]),"+f"(d[28]),"+f"(d[29]),"+f"(d[30]),"+f"(d[31]),"+f"(d[32]),"+f"(d[33]),"+f"(d[34]),"+f"(d[35]),"+f"(d[36]),"+f"(d[37]),"+f"(d[38]),"+f"(d[39]),"+f"(d[40]),"+f"(d[41]),"+f"(d[42]),"+f"(d[43]),"+f"(d[44]),"+f"(d[45]),"+f"(d[46]),"+f"(d[47]),"+f"(d[48]),"+f"(d[49]),"+f"(d[50]),"+f"(d[51]),"+f"(d[52]),"+f"(d[53]),"+f"(d[54]),"+f"(d[55]),"+f"(d[56]),"+f"(d[57]),"+f"(d[58]),"+f"(d[59]),"+f"(d[60]),"+f"(d[61]),"+f"(d[62]),"+f"(d[63]),"+f"(d[64]),"+f"(d[65]),"+f"(d[66]),"+f"(d[67]),"+f"(d[68]),"+f"(d[69]),"+f"(d[70]),"+f"(d[71]),"+f"(d[72]),"+f"(d[73]),"+f"(d[74]),"+f"(d[75]),"+f"(d[76]),"+f"(d[77]),"+f"(d[78]),"+f"(d[79])
    : "l"(da), "l"(db), "r"(sd));
}
__device__ __forceinline__ void wgmma_ss(float (&d)[108], uint64_t da, uint64_t db, int sd) {
  asm volatile("{\n.reg .pred p;\nsetp.ne.b32 p, %110, 0;\n"
    "wgmma.mma_async.sync.aligned.m64n216k16.f32.bf16.bf16 "
    "{%0,%1,%2,%3,%4,%5,%6,%7,%8,%9,%10,%11,%12,%13,%14,%15,%16,%17,%18,%19,%20,%21,%22,%23,%24,%25,%26,%27,%28,%29,%30,%31,%32,%33,%34,%35,%36,%37,%38,%39,%40,%41,%42,%43,%44,%45,%46,%47,%48,%49,%50,%51,%52,%53,%54,%55,%56,%57,%58,%59,%60,%61,%62,%63,%64,%65,%66,%67,%68,%69,%70,%71,%72,%73,%74,%75,%76,%77,%78,%79,%80,%81,%82,%83,%84,%85,%86,%87,%88,%89,%90,%91,%92,%93,%94,%95,%96,%97,%98,%99,%100,%101,%102,%103,%104,%105,%106,%107}, "
    "%108, %109, p, 1, 1, 0, 1;\n}\n"
    : "+f"(d[0]),"+f"(d[1]),"+f"(d[2]),"+f"(d[3]),"+f"(d[4]),"+f"(d[5]),"+f"(d[6]),"+f"(d[7]),"+f"(d[8]),"+f"(d[9]),"+f"(d[10]),"+f"(d[11]),"+f"(d[12]),"+f"(d[13]),"+f"(d[14]),"+f"(d[15]),"+f"(d[16]),"+f"(d[17]),"+f"(d[18]),"+f"(d[19]),"+f"(d[20]),"+f"(d[21]),"+f"(d[22]),"+f"(d[23]),"+f"(d[24]),"+f"(d[25]),"+f"(d[26]),"+f"(d[27]),"+f"(d[28]),"+f"(d[29]),"+f"(d[30]),"+f"(d[31]),"+f"(d[32]),"+f"(d[33]),"+f"(d[34]),"+f"(d[35]),"+f"(d[36]),"+f"(d[37]),"+f"(d[38]),"+f"(d[39]),"+f"(d[40]),"+f"(d[41]),"+f"(d[42]),"+f"(d[43]),"+f"(d[44]),"+f"(d[45]),"+f"(d[46]),"+f"(d[47]),"+f"(d[48]),"+f"(d[49]),"+f"(d[50]),"+f"(d[51]),"+f"(d[52]),"+f"(d[53]),"+f"(d[54]),"+f"(d[55]),"+f"(d[56]),"+f"(d[57]),"+f"(d[58]),"+f"(d[59]),"+f"(d[60]),"+f"(d[61]),"+f"(d[62]),"+f"(d[63]),"+f"(d[64]),"+f"(d[65]),"+f"(d[66]),"+f"(d[67]),"+f"(d[68]),"+f"(d[69]),"+f"(d[70]),"+f"(d[71]),"+f"(d[72]),"+f"(d[73]),"+f"(d[74]),"+f"(d[75]),"+f"(d[76]),"+f"(d[77]),"+f"(d[78]),"+f"(d[79]),"+f"(d[80]),"+f"(d[81]),"+f"(d[82]),"+f"(d[83]),"+f"(d[84]),"+f"(d[85]),"+f"(d[86]),"+f"(d[87]),"+f"(d[88]),"+f"(d[89]),"+f"(d[90]),"+f"(d[91]),"+f"(d[92]),"+f"(d[93]),"+f"(d[94]),"+f"(d[95]),"+f"(d[96]),"+f"(d[97]),"+f"(d[98]),"+f"(d[99]),"+f"(d[100]),"+f"(d[101]),"+f"(d[102]),"+f"(d[103]),"+f"(d[104]),"+f"(d[105]),"+f"(d[106]),"+f"(d[107])
    : "l"(da), "l"(db), "r"(sd));
}
__device__ __forceinline__ void wgmma_ss(float (&d)[120], uint64_t da, uint64_t db, int sd) {
  asm volatile("{\n.reg .pred p;\nsetp.ne.b32 p, %122, 0;\n"
    "wgmma.mma_async.sync.aligned.m64n240k16.f32.bf16.bf16 "
    "{%0,%1,%2,%3,%4,%5,%6,%7,%8,%9,%10,%11,%12,%13,%14,%15,%16,%17,%18,%19,%20,%21,%22,%23,%24,%25,%26,%27,%28,%29,%30,%31,%32,%33,%34,%35,%36,%37,%38,%39,%40,%41,%42,%43,%44,%45,%46,%47,%48,%49,%50,%51,%52,%53,%54,%55,%56,%57,%58,%59,%60,%61,%62,%63,%64,%65,%66,%67,%68,%69,%70,%71,%72,%73,%74,%75,%76,%77,%78,%79,%80,%81,%82,%83,%84,%85,%86,%87,%88,%89,%90,%91,%92,%93,%94,%95,%96,%97,%98,%99,%100,%101,%102,%103,%104,%105,%106,%107,%108,%109,%110,%111,%112,%113,%114,%115,%116,%117,%118,%119}, "
    "%120, %121, p, 1, 1, 0, 1;\n}\n"
    : "+f"(d[0]),"+f"(d[1]),"+f"(d[2]),"+f"(d[3]),"+f"(d[4]),"+f"(d[5]),"+f"(d[6]),"+f"(d[7]),"+f"(d[8]),"+f"(d[9]),"+f"(d[10]),"+f"(d[11]),"+f"(d[12]),"+f"(d[13]),"+f"(d[14]),"+f"(d[15]),"+f"(d[16]),"+f"(d[17]),"+f"(d[18]),"+f"(d[19]),"+f"(d[20]),"+f"(d[21]),"+f"(d[22]),"+f"(d[23]),"+f"(d[24]),"+f"(d[25]),"+f"(d[26]),"+f"(d[27]),"+f"(d[28]),"+f"(d[29]),"+f"(d[30]),"+f"(d[31]),"+f"(d[32]),"+f"(d[33]),"+f"(d[34]),"+f"(d[35]),"+f"(d[36]),"+f"(d[37]),"+f"(d[38]),"+f"(d[39]),"+f"(d[40]),"+f"(d[41]),"+f"(d[42]),"+f"(d[43]),"+f"(d[44]),"+f"(d[45]),"+f"(d[46]),"+f"(d[47]),"+f"(d[48]),"+f"(d[49]),"+f"(d[50]),"+f"(d[51]),"+f"(d[52]),"+f"(d[53]),"+f"(d[54]),"+f"(d[55]),"+f"(d[56]),"+f"(d[57]),"+f"(d[58]),"+f"(d[59]),"+f"(d[60]),"+f"(d[61]),"+f"(d[62]),"+f"(d[63]),"+f"(d[64]),"+f"(d[65]),"+f"(d[66]),"+f"(d[67]),"+f"(d[68]),"+f"(d[69]),"+f"(d[70]),"+f"(d[71]),"+f"(d[72]),"+f"(d[73]),"+f"(d[74]),"+f"(d[75]),"+f"(d[76]),"+f"(d[77]),"+f"(d[78]),"+f"(d[79]),"+f"(d[80]),"+f"(d[81]),"+f"(d[82]),"+f"(d[83]),"+f"(d[84]),"+f"(d[85]),"+f"(d[86]),"+f"(d[87]),"+f"(d[88]),"+f"(d[89]),"+f"(d[90]),"+f"(d[91]),"+f"(d[92]),"+f"(d[93]),"+f"(d[94]),"+f"(d[95]),"+f"(d[96]),"+f"(d[97]),"+f"(d[98]),"+f"(d[99]),"+f"(d[100]),"+f"(d[101]),"+f"(d[102]),"+f"(d[103]),"+f"(d[104]),"+f"(d[105]),"+f"(d[106]),"+f"(d[107]),"+f"(d[108]),"+f"(d[109]),"+f"(d[110]),"+f"(d[111]),"+f"(d[112]),"+f"(d[113]),"+f"(d[114]),"+f"(d[115]),"+f"(d[116]),"+f"(d[117]),"+f"(d[118]),"+f"(d[119])
    : "l"(da), "l"(db), "r"(sd));
}

constexpr int PH_WO = 1, PH_W1 = 2, PH_W2 = 4, PH_QKV = 8;
constexpr int SA = 4, SB = 5;
constexpr int A_STAGE = 16384, B_STAGE = 32768;
constexpr int SM_B = SA * A_STAGE;
constexpr int SM_CS = SM_B + SB * B_STAGE;
constexpr int SM_B1 = SM_CS + 960;
constexpr int SM_ROW = SM_B1 + 864;
constexpr int SM_BAR = SM_ROW + 1024;
constexpr int CHAIN_SMEM = SM_BAR + 224;
static_assert(CHAIN_SMEM <= 232448, "shared memory");
constexpr int FIRST_THREADS = 384;
constexpr int CHAIN_THREADS = 352;
constexpr int BAR_FA = 0, BAR_EA = SA * 8, BAR_FB = 2 * SA * 8, BAR_EB = (2 * SA + SB) * 8, BAR_AUX = (2 * SA + 2 * SB) * 8, BAR_JOB = BAR_AUX + 16, BAR_GO = BAR_AUX + 40, BAR_TILE = BAR_AUX + 48;

struct alignas(64) ChainParams {
  CUtensorMap a_x, b_wo, b_w1, b_w2, b_wqkv, o_out;
  const bf16* xres;
  const bf16* xin;
  const bf16 *b1, *b2;
  unsigned int* flags;
  int kid;
  signed char pref[160];
};

struct Ring { uint32_t s, ph; };
template <int N> __device__ __forceinline__ void ring_adv(Ring& r) { if (++r.s == N) { r.s = 0; r.ph ^= 1; } }

template <int KT, int BYTES, int N, int STAGE>
__device__ __forceinline__ void produce(const void* src, uint32_t dst, uint32_t full, uint32_t empty, Ring& r) {
#pragma unroll 1
  for (int kt = 0; kt < KT; kt++) {
    mbar_wait(empty + r.s * 8, r.ph ^ 1);
    mbar_expect_tx(full + r.s * 8, BYTES);
    bulk_g2s(dst + r.s * STAGE, (const uint8_t*)src + kt * BYTES, BYTES, full + r.s * 8);
    ring_adv<N>(r);
  }
}
__device__ __forceinline__ void bulk_s2g(void* dst, uint32_t src, uint32_t bytes) {
  asm volatile("cp.async.bulk.global.shared::cta.bulk_group [%0], [%1], %2;\ncp.async.bulk.commit_group;" ::"l"(dst), "r"(src), "r"(bytes) : "memory");
}
template <int BN, int KT, int BK, bool TILED, bool SPLIT, bool B128>
__device__ __forceinline__ void mainloop(float (&acc)[BN / 2], uint32_t sbase, uint32_t bars, int wg, int lane, Ring& ra, Ring& rb) {
  uint32_t pa = 0, pb = 0;
  constexpr int NS = SPLIT ? BK / 32 : BK / 16, ST = SPLIT ? 2 : 1;
  const uint32_t aoff = SPLIT ? wg * 256 : wg * 8192, boff = SPLIT ? wg * 1024 : 0;
#pragma unroll 1
  for (int kt = 0; kt < KT; kt++) {
    mbar_wait(bars + BAR_FB + rb.s * 8, rb.ph);
    mbar_wait(bars + BAR_FA + ra.s * 8, ra.ph);
    const uint64_t da = TILED ? mk_desc(sbase + ra.s * A_STAGE + aoff, 128, BK * 16, 0) : mk_desc(sbase + ra.s * A_STAGE + aoff, 16, 1024, 1);
    const uint64_t db = B128 ? mk_desc(sbase + SM_B + rb.s * B_STAGE, 8192, 1024, 1) : mk_desc(sbase + SM_B + rb.s * B_STAGE + boff, BK * 64, 512, 2);
    wg_fence();
#pragma unroll
    for (int k = 0; k < NS; k++) wgmma_ss(acc, da + k * ST * (TILED ? 16 : 2), db + k * ST * (B128 ? 128 : 64), (kt | k) != 0);
    wg_commit();
    wg_wait<1>();
    if (kt > 0 && lane == 0) { mbar_arrive(bars + BAR_EA + pa); mbar_arrive(bars + BAR_EB + pb); }
    pa = ra.s * 8; pb = rb.s * 8;
    ring_adv<SA>(ra);
    ring_adv<SB>(rb);
  }
  wg_wait<0>();
  fence_regs(acc);
  if (lane == 0) { mbar_arrive(bars + BAR_EA + pa); mbar_arrive(bars + BAR_EB + pb); }
}

__device__ __forceinline__ void exchange(float (&acc)[80], float (&own)[40], uint8_t* smem, int wg, int tid) {
  named_bar(1, 256);
  float4* w = (float4*)smem + (tid ^ 128);
#pragma unroll
  for (int b = 0; b < 10; b++) {
    float v[4];
#pragma unroll
    for (int e = 0; e < 4; e++) { v[e] = wg ? acc[4 * b + e] : acc[40 + 4 * b + e]; own[4 * b + e] = wg ? acc[40 + 4 * b + e] : acc[4 * b + e]; }
    w[b * 256] = make_float4(v[0], v[1], v[2], v[3]);
  }
  named_bar(1, 256);
#pragma unroll
  for (int b = 0; b < 10; b++) {
    const float4 v = ((const float4*)smem)[b * 256 + tid];
    own[4 * b] += v.x; own[4 * b + 1] += v.y; own[4 * b + 2] += v.z; own[4 * b + 3] += v.w;
  }
  asm volatile("fence.proxy.async.shared::cta;" ::: "memory");
}

template <bool BIAS, bool FINAL>
__device__ __forceinline__ void epi_resid(const float (&acc)[40], uint32_t (&res)[20], const uint32_t (&bias)[10], bf16* out, float2* st,
                                          uint8_t* stage, int row0, int rl, int j, int lane) {
  const int q = lane & 3;
  uint32_t* o0 = FINAL ? (uint32_t*)(stage + rl * 320 + (j & 1) * 160) + q : (uint32_t*)out + lane;
  float s0 = 0.f, t0 = 0.f, s1 = 0.f, t1 = 0.f;
#pragma unroll
  for (int b = 0; b < 10; b++) {
    const float bl = BIAS ? bf_lo(bias[b]) : 0.f, bh = BIAS ? bf_hi(bias[b]) : 0.f;
    const uint32_t p0 = pack_bf16(acc[4 * b] + bl + bf_lo(res[2 * b]), acc[4 * b + 1] + bh + bf_hi(res[2 * b]));
    const uint32_t p1 = pack_bf16(acc[4 * b + 2] + bl + bf_lo(res[2 * b + 1]), acc[4 * b + 3] + bh + bf_hi(res[2 * b + 1]));
    res[2 * b] = p0; res[2 * b + 1] = p1;
    if (FINAL) { o0[b * 4] = p0; o0[b * 4 + 640] = p1; }
    else {
      const int ln = x_line(row0, j * 10 + b);
      o0[ln * 32] = p0; o0[ln * 32 + 256] = p1;
      const float a = bf_lo(p0), c = bf_hi(p0), d = bf_lo(p1), e = bf_hi(p1);
      s0 += a + c; t0 = fmaf(a, a, fmaf(c, c, t0));
      s1 += d + e; t1 = fmaf(d, d, fmaf(e, e, t1));
    }
  }
  if (!FINAL) {
#pragma unroll
    for (int m = 1; m < 4; m <<= 1) {
      s0 += __shfl_xor_sync(0xffffffffu, s0, m); t0 += __shfl_xor_sync(0xffffffffu, t0, m);
      s1 += __shfl_xor_sync(0xffffffffu, s1, m); t1 += __shfl_xor_sync(0xffffffffu, t1, m);
    }
    if (q < 2) st[j * SEQ + row0 + q * 8] = q ? make_float2(s1, t1) : make_float2(s0, t0);
  }
}
__device__ __forceinline__ void publish(unsigned int* f, int lane, uint32_t go) {
  __syncwarp();
  if (lane == 0) { flag_signal(f); mbar_arrive(go); }
}
__device__ __forceinline__ float gelu_half(float s) {
  const float z = s * fmaf(s * s, 8.f * 0.044715f * 0.7978845608028654f, 2.f * 0.7978845608028654f);
  float th;
  asm("tanh.approx.f32 %0, %1;" : "=f"(th) : "f"(z));
  return fmaf(s, th, s);
}
template <bool DOUBLE> __device__ __forceinline__ float2 row_coef(float s, float t) {
  const float mean = s * (1.f / DM);
  const float var = fmaxf(fmaf(-mean, mean, t * (1.f / DM)), 0.f);
  float r = rsqrtf(var + LN_EPS);
  if (DOUBLE) r *= 0.5f * rsqrtf(var * r * r + LN_EPS);
  return make_float2(r, -r * mean);
}
template <int ROWS, int PITCH> __device__ __forceinline__ void colsum_tile(float (&c)[8], const uint8_t* base, int g, int r0) {
#pragma unroll
  for (int e = 0; e < 8; e++) c[e] = 0.f;
#pragma unroll 4
  for (int r = 0; r < ROWS; r++) {
    const int x = PITCH == 128 ? (g ^ ((r0 + r) & 7)) : (g ^ (((r0 + r) >> 1) & 3));
    const uint4 v = *(const uint4*)(base + r * PITCH + x * 16);
    c[0] += bf_lo(v.x); c[1] += bf_hi(v.x); c[2] += bf_lo(v.y); c[3] += bf_hi(v.y);
    c[4] += bf_lo(v.z); c[5] += bf_hi(v.z); c[6] += bf_lo(v.w); c[7] += bf_hi(v.w);
  }
}
template <int N, int NP> __device__ __forceinline__ void reduce_colsum(const float* part, int ld, float* dst, float* gdst, int lane) {
  float4 v[2][NP];
#pragma unroll
  for (int rr = 0; rr < 2; rr++)
#pragma unroll
    for (int p = 0; p < NP; p++) v[rr][p] = rr * 128 + lane * 4 < N ? __ldcg((const float4*)(part + p * ld + rr * 128 + lane * 4)) : make_float4(0.f, 0.f, 0.f, 0.f);
#pragma unroll
  for (int rr = 0; rr < 2; rr++) {
    float4 a = make_float4(0.f, 0.f, 0.f, 0.f);
#pragma unroll
    for (int p = 0; p < NP; p++) { a.x += v[rr][p].x; a.y += v[rr][p].y; a.z += v[rr][p].z; a.w += v[rr][p].w; }
    if (rr * 128 + lane * 4 < N) {
      if (dst) *(float4*)(dst + rr * 128 + lane * 4) = a;
      if (gdst) *(float4*)(gdst + rr * 128 + lane * 4) = a;
    }
  }
}
template <bool DOUBLE, int NP> __device__ __forceinline__ void reduce_stats(const float2* st, float2* dst, int i, int lane) {
  float4 v[2][NP];
#pragma unroll
  for (int rr = 0; rr < 2; rr++)
#pragma unroll
    for (int k = 0; k < NP; k++) v[rr][k] = __ldcg((const float4*)(st + k * SEQ + i * 128 + rr * 64) + lane);
#pragma unroll
  for (int rr = 0; rr < 2; rr++) {
    float s0 = 0.f, t0 = 0.f, s1 = 0.f, t1 = 0.f;
#pragma unroll
    for (int k = 0; k < NP; k++) { s0 += v[rr][k].x; t0 += v[rr][k].y; s1 += v[rr][k].z; t1 += v[rr][k].w; }
    dst[rr * 64 + lane * 2] = row_coef<DOUBLE>(s0, t0);
    dst[rr * 64 + lane * 2 + 1] = row_coef<DOUBLE>(s1, t1);
  }
}

template <int PH, bool FIRST, bool LAST>
__global__ void __launch_bounds__(FIRST ? FIRST_THREADS : CHAIN_THREADS, 1) chain_kernel(const __grid_constant__ ChainParams p) {
  extern __shared__ __align__(1024) uint8_t smem[];
  const uint32_t sbase = smem_u32(smem), bars = sbase + SM_BAR;
  float* cs = (float*)(smem + SM_CS);
  float* sb1 = (float*)(smem + SM_B1);
  float2* srow = (float2*)(smem + SM_ROW);
  const int tid = threadIdx.x, lane = tid & 31, warp = __shfl_sync(0xffffffffu, tid >> 5, 0);
  if (tid == 32) {
    unsigned int* claim = p.flags + 64;
    uint32_t smid;
    asm volatile("mov.u32 %0, %%smid;" : "=r"(smid));
    int t = smid < 160 ? p.pref[smid] : -1;
    if (t >= 0 && atomicExch(claim + t, 1u) != 0u) t = -2;
    if (t == -1) {
#pragma unroll 1
      for (int it = 0; it < 100000; it++) {
        if (*(volatile unsigned int*)(claim + 128) >= 128u) break;
        __nanosleep(200);
      }
    }
    if (t < 0) {
      t = -1;
      if (*(volatile unsigned int*)(claim + 128) < 128u) {
#pragma unroll 1
        for (int c = 0; c < 128 && t < 0; c++)
          if (atomicExch(claim + c, 1u) == 0u) t = c;
      }
    }
    if (t >= 0) atomicAdd(claim + 128, 1u);
    *(volatile int*)(smem + SM_BAR + BAR_TILE) = t;
  }
  unsigned int* fl = p.flags;
  if (tid == 0) {
    for (int s = 0; s < SA; s++) { mbar_init(bars + BAR_FA + s * 8, 1); mbar_init(bars + BAR_EA + s * 8, 8); }
    for (int s = 0; s < SB; s++) { mbar_init(bars + BAR_FB + s * 8, 1); mbar_init(bars + BAR_EB + s * 8, 8); }
    mbar_init(bars + BAR_AUX, 32); mbar_init(bars + BAR_AUX + 8, FIRST ? 33 : 32);
    mbar_init(bars + BAR_GO, 8);
    mbar_init(bars + BAR_JOB, 1); mbar_init(bars + BAR_JOB + 8, 1); mbar_init(bars + BAR_JOB + 16, 1);
    asm volatile("fence.mbarrier_init.release.cluster;" ::: "memory");
  }
  if (tid == 256) {
    if (FIRST) { prefetch_map(&p.a_x); prefetch_map(&p.b_wqkv); }
    if (LAST) prefetch_map(&p.o_out);
  }
  __syncthreads();
  pdl_launch();
  const int tile = *(volatile int*)(smem + SM_BAR + BAR_TILE);
  if (tile < 0) return;
  const int i = tile >> 3, j = tile & 7;
  if (tid == 0) TS(p.kid, 0);

  if (warp == 9) {
    if (lane == 0) {
      Ring r{0, 0};
      if (FIRST) {
#pragma unroll 1
        for (int kt = 0; kt < 10; kt++) {
          if (kt == 0) {
            mbar_expect_tx(bars + BAR_JOB + 16, 32768);
#pragma unroll 1
            for (int b = 0; b < 4; b++) tma_3d(sbase + SM_B + (SB - 1) * B_STAGE + b * 8192, &p.b_wqkv, b * 64, j, i * 40, bars + BAR_JOB + 16);
          }
          if (kt == SB - 1) mbar_wait(bars + BAR_GO, 0);
          mbar_wait(bars + BAR_EB + r.s * 8, r.ph ^ 1);
          if (kt == i + SB) asm volatile("cp.async.bulk.wait_group.read 0;" ::: "memory");
          mbar_expect_tx(bars + BAR_FB + r.s * 8, 32768);
#pragma unroll 1
          for (int b = 0; b < 4; b++) tma_3d(sbase + SM_B + r.s * B_STAGE + b * 8192, &p.b_wqkv, b * 64, j, kt * 64, bars + BAR_FB + r.s * 8);
          if (kt == SB - 1 + (i >= SB ? SB : 0) && i < 10) {
            mbar_wait(bars + BAR_FB + (i % SB) * 8, i / SB);
            bulk_s2g(g_wt + WT_QKV + (j * 10 + i) * 32768, sbase + SM_B + (i % SB) * B_STAGE, 32768);
          }
          ring_adv<SB>(r);
        }
        asm volatile("cp.async.bulk.wait_group.read 0;" ::: "memory");
        mbar_arrive(bars + BAR_AUX + 8);
#pragma unroll 1
        for (int n = 0; n < 2; n++) {
          const int job = n * 128 + tile;
          if (job < 192) {
            const uint32_t st = sbase + SM_B + (1 + n) * B_STAGE, bar = bars + BAR_JOB + n * 8;
            mbar_wait(bars + BAR_EB + (1 + n) * 8, 1);
            const CUtensorMap* m = job < 40 ? &p.b_wo : (job < 120 ? &p.b_w1 : &p.b_w2);
            const int t = job < 40 ? job : (job < 120 ? job - 40 : job - 120);
            const int nkt = job < 120 ? 10 : 18, bk = job < 120 ? 64 : 96, nbox = (job >= 40 && job < 120) ? 7 : 5;
            mbar_expect_tx(bar, nbox * bk * 64);
#pragma unroll 1
            for (int b = 0; b < nbox; b++) tma_3d(st + b * bk * 64, m, b * 32, t / nkt, (t % nkt) * bk, bar);
          }
        }
#pragma unroll 1
        for (int n = 0; n < 2; n++) {
          const int job = n * 128 + tile;
          if (job < 192) {
            mbar_wait(bars + BAR_JOB + n * 8, 0);
            const int off = job < 40 ? WT_WO + job * 20480 : (job < 120 ? WT_W1 + (job - 40) * 28672 : WT_W2 + (job - 120) * 30720);
            bulk_s2g(g_wt + off, sbase + SM_B + (1 + n) * B_STAGE, job < 40 ? 20480 : (job < 120 ? 28672 : 30720));
          }
        }
        asm volatile("cp.async.bulk.wait_group 0;" ::: "memory");
      } else {
        if (PH & PH_WO) produce<10, 20480, SB, B_STAGE>(g_wt + WT_WO + (j >> 1) * 10 * 20480, sbase + SM_B, bars + BAR_FB, bars + BAR_EB, r);
        if (GATE & 1) mbar_wait(bars + BAR_GO, 0);
        if (PH & PH_W1) produce<10, 28672, SB, B_STAGE>(g_wt + WT_W1 + j * 10 * 28672, sbase + SM_B, bars + BAR_FB, bars + BAR_EB, r);
        if (GATE & 2) mbar_wait(bars + BAR_GO, 1);
        if (PH & PH_W2) produce<18, 30720, SB, B_STAGE>(g_wt + WT_W2 + (j >> 1) * 18 * 30720, sbase + SM_B, bars + BAR_FB, bars + BAR_EB, r);
        if ((GATE & 4) && (PH & PH_QKV)) mbar_wait(bars + BAR_GO, 0);
        if (PH & PH_QKV) produce<10, 32768, SB, B_STAGE>(g_wt + WT_QKV + j * 10 * 32768, sbase + SM_B, bars + BAR_FB, bars + BAR_EB, r);
      }
    }
  } else if (warp == 8) {
    if (lane == 0) {
      Ring r{0, 0};
      if (FIRST) {
#pragma unroll 1
        for (int kt = 0; kt < 10; kt++) {
          mbar_wait(bars + BAR_EA + r.s * 8, r.ph ^ 1);
          mbar_expect_tx(bars + BAR_FA + r.s * 8, A_STAGE);
          tma_2d(sbase + r.s * A_STAGE, &p.a_x, kt * 64, i * 128, bars + BAR_FA + r.s * 8);
          ring_adv<SA>(r);
        }
      } else {
        const int ih = i * 2 + (j & 1);
        pdl_wait();
        TS(p.kid, 16);
        produce<10, 8192, SA, A_STAGE>((const uint8_t*)g_o + ih * 10 * 8192, sbase, bars + BAR_FA, bars + BAR_EA, r);
        flag_wait(fl + i, 64); fence_async_global(); TS(p.kid, 17);
        produce<10, 16384, SA, A_STAGE>((const uint8_t*)g_x1 + i * 10 * 16384, sbase, bars + BAR_FA, bars + BAR_EA, r);
        flag_wait(fl + 16 + i, 64); fence_async_global(); TS(p.kid, 18);
        produce<18, 12288, SA, A_STAGE>((const uint8_t*)g_h + ih * 18 * 12288, sbase, bars + BAR_FA, bars + BAR_EA, r);
        if (PH & PH_QKV) {
          flag_wait(fl + 32 + i, 64); fence_async_global(); TS(p.kid, 19);
          produce<10, 16384, SA, A_STAGE>((const uint8_t*)g_x2 + i * 10 * 16384, sbase, bars + BAR_FA, bars + BAR_EA, r);
        }
      }
    }
  } else if (warp >= 10) {
    if (FIRST) {
      const int w = warp - 10;
      float c[8];
      if (w == 0) {
        named_bar(4, 288);
        if (lane == 0) { asm volatile("fence.acq_rel.gpu;" ::: "memory"); atomicAdd(fl + i, 1u); atomicAdd(fl + 16 + j, 1u); TS(p.kid, 20); }
      }
      if (w == 0) {
        if (lane == 0) flag_wait(fl + 16 + j, 16);
        __syncwarp();
        reduce_colsum<240, 16>(g_s.csp_qkv + j * 240, 1920, cs, i == 0 ? g_s.cs_qkv + j * 240 : nullptr, lane);
        if (lane == 0) flag_wait(fl + i, 8);
        __syncwarp();
        reduce_stats<false, 4>(g_s.st0, srow, i, lane);
        if (lane == 0) TS(p.kid, 22);
        mbar_arrive(bars + BAR_AUX + 8);
      } else if (tile >= 40 && tile < 120) {
        mbar_wait(bars + BAR_JOB, 0);
        colsum_tile<64, 64>(c, smem + SM_B + B_STAGE + (lane >> 2) * 4096, lane & 3, 0);
        const int t = tile - 40;
        if (lane < 27) {
          float4* d = (float4*)(g_s.csp_w1 + (t % 10) * FF + (t / 10) * 216 + lane * 8);
          d[0] = make_float4(c[0], c[1], c[2], c[3]); d[1] = make_float4(c[4], c[5], c[6], c[7]);
        }
      }
    } else {
      if (PH & PH_W1) {
        reduce_colsum<216, 10>(g_s.csp_w1 + j * 216, FF, cs, nullptr, lane);
        for (int c = lane; c < 216; c += 32) sb1[c] = 0.5f * __bfloat162float(p.b1[j * 216 + c]);
        pdl_wait();
        if (lane == 0) flag_wait(fl + i, 64);
        __syncwarp();
        reduce_stats<true, 8>(g_s.st1, srow, i, lane);
        mbar_arrive(bars + BAR_AUX);
      }
      if (PH & PH_QKV) {
        float cq[8];
#pragma unroll
        for (int k = 0; k < 8; k++) cq[k] = k * 32 + lane < 240 ? __ldcg(g_s.cs_qkv + j * 240 + k * 32 + lane) : 0.f;
        if (lane == 0) flag_wait(fl + 32 + i, 64);
        __syncwarp();
#pragma unroll
        for (int k = 0; k < 8; k++) if (k * 32 + lane < 240) cs[k * 32 + lane] = cq[k];
        reduce_stats<false, 8>(g_s.st2, srow, i, lane);
        if (lane == 0) TS(p.kid, 22);
        mbar_arrive(bars + BAR_AUX + 8);
      }
    }
  } else {
    const int wg = warp >> 2, q = lane & 3;
    const int rl = wg * 64 + (warp & 3) * 16 + (lane >> 2);
    const int row0 = i * 128 + rl;
    const int rs = (warp & 3) * 16 + (lane >> 2), rowS = i * 128 + (j & 1) * 64 + rs, jS = (j & 6) + wg;
    Ring ra{0, 0}, rb{0, 0};
    uint32_t res[20], bias2[10];
    if (FIRST) {
      const int xrow = i * 128 + j * 16 + (warp & 1) * 8 + (lane >> 2), xcg = (warp >> 1) * 20 + q;
      uint4 xv[5];
#pragma unroll
      for (int k = 0; k < 5; k++) xv[k] = __ldg((const uint4*)(p.xin + (size_t)xrow * DM) + xcg + k * 4);
      float c[8];
      uint8_t* slab = smem + SM_B + (SB - 1) * B_STAGE;
      mbar_wait(bars + BAR_JOB + 16, 0);
      colsum_tile<5, 128>(c, slab + (lane >> 3) * 8192 + warp * 5 * 128, lane & 7, warp * 5);
      float4* part = (float4*)(slab + 5120 + (warp & 1) * 1024 + (warp >> 1) * 8192) + lane * 2;
      part[0] = make_float4(c[0], c[1], c[2], c[3]); part[1] = make_float4(c[4], c[5], c[6], c[7]);
      float xs = 0.f, xt = 0.f;
#pragma unroll
      for (int k = 0; k < 5; k++) {
        const uint32_t e[4] = {xv[k].x, xv[k].y, xv[k].z, xv[k].w};
#pragma unroll
        for (int m = 0; m < 4; m++) { const float a = bf_lo(e[m]), b = bf_hi(e[m]); xs += a + b; xt = fmaf(a, a, fmaf(b, b, xt)); }
        *((uint4*)g_x0 + x_line(xrow, xcg + k * 4) * 8 + (xrow & 7)) = xv[k];
      }
#pragma unroll
      for (int m = 1; m < 4; m <<= 1) { xs += __shfl_xor_sync(0xffffffffu, xs, m); xt += __shfl_xor_sync(0xffffffffu, xt, m); }
      if (q == 0) g_s.st0[(warp >> 1) * SEQ + xrow] = make_float2(xs, xt);
      named_bar(1, 256);
      if (tid < 240) {
        float a = 0.f;
#pragma unroll
        for (int k = 0; k < 8; k++) a += *(const float*)(slab + 5120 + (k & 1) * 1024 + (k >> 1) * 8192 + tid * 4);
        g_s.csp_qkv[i * 1920 + j * 240 + tid] = a;
      }
      asm volatile("fence.proxy.async.shared::cta;" ::: "memory");
      __syncwarp();
      if (lane == 0) mbar_arrive(bars + BAR_GO);
      asm volatile("bar.arrive 4, 288;" ::: "memory");
    }
    if (PH & PH_WO) {
#pragma unroll
      for (int b = 0; b < 10; b++) {
        const uint32_t* r0 = (const uint32_t*)p.xres + x_line(rowS, jS * 10 + b) * 32 + lane;
        res[2 * b] = __ldcg(r0); res[2 * b + 1] = __ldcg(r0 + 256);
      }
    }
    if (PH & PH_WO) {
      float acc[80], own[40];
      if (tid == 0) TS(p.kid, 1);
      mainloop<160, 10, 64, true, true, false>(acc, sbase, bars, wg, lane, ra, rb);
      if (tid == 0) TS(p.kid, 2);
      exchange(acc, own, smem, wg, tid);
      if (tid == 0) TS(p.kid, 3);
      pdl_wait();
      epi_resid<false, false>(own, res, bias2, g_x1, g_s.st1, smem, rowS, rs, jS, lane);
      publish(fl + i, lane, bars + BAR_GO);
    }
    if (PH & PH_W1) {
      float acc[108];
      if (tid == 0) TS(p.kid, 4);
      mainloop<216, 10, 64, true, false, false>(acc, sbase, bars, wg, lane, ra, rb);
      if (tid == 0) TS(p.kid, 5);
      mbar_wait(bars + BAR_AUX, 0);
      const float2 c0 = srow[rl], c1 = srow[rl + 8];
      uint32_t* o0 = (uint32_t*)g_h + h_line(row0, j * 27) * 32 + lane;
      int kg = (j * 27) % 12;
#pragma unroll
      for (int b = 0; b < 27; b++) {
        const float2 cc = *(const float2*)(cs + b * 8 + q * 2), bb = *(const float2*)(sb1 + b * 8 + q * 2);
        o0[0] = pack_bf16(gelu_half(fmaf(c0.x, acc[4 * b], fmaf(c0.y, cc.x, bb.x))), gelu_half(fmaf(c0.x, acc[4 * b + 1], fmaf(c0.y, cc.y, bb.y))));
        o0[384] = pack_bf16(gelu_half(fmaf(c1.x, acc[4 * b + 2], fmaf(c1.y, cc.x, bb.x))), gelu_half(fmaf(c1.x, acc[4 * b + 3], fmaf(c1.y, cc.y, bb.y))));
        o0 += (++kg == 12) ? (96 - 11) * 32 : 32;
        if (kg == 12) kg = 0;
      }
      if (tid == 0) TS(p.kid, 6);
      publish(fl + 16 + i, lane, bars + BAR_GO);
    }
    if (PH & PH_W2) {
#pragma unroll
      for (int b = 0; b < 10; b++) bias2[b] = __ldg((const uint32_t*)(p.b2 + jS * 80) + b * 4 + q);
      float acc[80], own[40];
      if (tid == 0) TS(p.kid, 7);
      mainloop<160, 18, 96, true, true, false>(acc, sbase, bars, wg, lane, ra, rb);
      if (tid == 0) TS(p.kid, 8);
      exchange(acc, own, smem, wg, tid);
      if (tid == 0) TS(p.kid, 9);
      if (LAST) {
        epi_resid<true, true>(own, res, bias2, nullptr, nullptr, smem + 40960, rowS, rs, jS, lane);
        asm volatile("fence.proxy.async.shared::cta;" ::: "memory");
        named_bar(1, 256);
        if (tid == 0) {
          asm volatile("cp.async.bulk.tensor.2d.global.shared::cta.bulk_group [%0, {%2, %3}], [%1];" ::"l"(&p.o_out), "r"(sbase + 40960), "r"((j >> 1) * 160), "r"(i * 128 + (j & 1) * 64) : "memory");
          asm volatile("cp.async.bulk.commit_group;\ncp.async.bulk.wait_group 0;" ::: "memory");
        }
      } else {
        epi_resid<true, false>(own, res, bias2, g_x2, g_s.st2, smem, rowS, rs, jS, lane);
        publish(fl + 32 + i, lane, bars + BAR_GO);
      }
    }
    if (PH & PH_QKV) {
      float acc[120];
      if (tid == 0) TS(p.kid, 10);
      mainloop<240, 10, 64, !FIRST, false, true>(acc, sbase, bars, wg, lane, ra, rb);
      if (tid == 0) TS(p.kid, 11);
      mbar_wait(bars + BAR_AUX + 8, 0);
      const float2 c0 = srow[rl], c1 = srow[rl + 8];
      const bool mu0 = is_mufu(row0 >> 3), mu1 = is_mufu((row0 >> 3) + 1);
      const float QS = 0.22360679774997896f * 1.4426950408889634f;
      const float ks0 = mu0 ? 1.f : 0x1p-22f, ks1 = mu1 ? 1.f : 0x1p-22f;
      unsigned int* smax = (unsigned int*)sb1;
      if (tid < 12) smax[tid] = 0u;
      named_bar(1, 256);
      uint8_t* stg = smem + warp * 9216 + (lane >> 2) * 16;
      int off[5];
#pragma unroll
      for (int m = 0; m < 5; m++) {
        const int c = m * 8 + q * 2, hh = c >= 20, d = c - hh * 20;
        off[m] = hh * 768 + (d >> 3) * 128 + (d & 7) * 2;
      }
      uint8_t* gdst = (uint8_t*)g_qkv + (size_t)(j * 12 + (lane & 1)) * HEAD_BYTES + (i * 16 + warp * 2) * 384;
#pragma unroll
      for (int pr = 0; pr < 6; pr++) {
        const int part = (j * 12 + pr * 2) >> 5;
        const float s0 = part == 0 ? QS : (part == 1 ? ks0 : 1.f), s1 = part == 0 ? QS : (part == 1 ? ks1 : 1.f);
        const float a0 = c0.x * s0, b0 = c0.y * s0, a1 = c1.x * s1, b1 = c1.y * s1;
        float nA0 = 0.f, nA1 = 0.f, nB0 = 0.f, nB1 = 0.f;
#pragma unroll
        for (int m = 0; m < 5; m++) {
          const int b = pr * 5 + m;
          const float2 cc = *(const float2*)(cs + b * 8 + q * 2);
          uint8_t* ptr = stg + off[m] + pr * 1536;
          const float v0 = fmaf(a0, acc[4 * b], b0 * cc.x), v1 = fmaf(a0, acc[4 * b + 1], b0 * cc.y);
          const float v2 = fmaf(a1, acc[4 * b + 2], b1 * cc.x), v3 = fmaf(a1, acc[4 * b + 3], b1 * cc.y);
          *(uint32_t*)ptr = pack_bf16(v0, v1);
          *(uint32_t*)(ptr + 384) = pack_bf16(v2, v3);
          const float n0 = fmaf(v0, v0, v1 * v1), n1 = fmaf(v2, v2, v3 * v3);
          if (m < 2) { nA0 += n0; nA1 += n1; } else if (m > 2) { nB0 += n0; nB1 += n1; }
          else if (q < 2) { nA0 += n0; nA1 += n1; } else { nB0 += n0; nB1 += n1; }
        }
        const bool mu = (q & 1) ? mu1 : mu0;
        const uint2 ex = part == 0 ? make_uint2(0x3F803F80u, 0x00003F80u)
                                   : (part == 1 ? (mu ? make_uint2(0u, 0u) : make_uint2(0x377C3C00u, 0x00003020u)) : make_uint2(0x00003F80u, 0u));
        *(uint2*)(stg + pr * 1536 + (q >> 1) * 768 + (q & 1) * 384 + 264) = ex;
        asm volatile("fence.proxy.async.shared::cta;" ::: "memory");
        __syncwarp();
        if (lane < 2) bulk_s2g(gdst + pr * 2 * HEAD_BYTES, sbase + warp * 9216 + pr * 1536 + lane * 768, 768);
        if (part < 2) {
          float x = (q & 1) ? nA1 : nA0, y = (q & 1) ? nB1 : nB0;
          x += __shfl_xor_sync(0xffffffffu, (q & 1) ? nA0 : nA1, 1);
          y += __shfl_xor_sync(0xffffffffu, (q & 1) ? nB0 : nB1, 1);
          float n = (q & 2) ? y : x;
          n += __shfl_xor_sync(0xffffffffu, (q & 2) ? x : y, 2);
          if (part == 1 && !mu) n *= 0x1p44f;
          atomicMax(smax + pr * 2 + (q >> 1), __float_as_uint(n) & 0x7FFFFFFFu);
        }
      }
      named_bar(1, 256);
      if (tid < 12 && j * 12 + tid < 64) atomicMax(fl + NORM_OFF + j * 12 + tid, smax[tid]);
      if (lane < 2) asm volatile("cp.async.bulk.wait_group 0;" ::: "memory");
    }
    if (tid == 0) TS(p.kid, 15);
  }
}

__device__ __forceinline__ uint32_t exp2_poly_pair(float a0, float a1) {
  const uint32_t v = __byte_perm(__float_as_uint(a0), __float_as_uint(a1), 0x7430);
  const uint32_t e = __byte_perm(__float_as_uint(a0), __float_as_uint(a1), 0x6521);
  uint32_t u;
  asm("fma.rn.f16x2 %0, %1, %2, %3;" : "=r"(u) : "r"(v), "r"(0x1d611d61u), "r"(0xa012a012u));
  asm("fma.rn.f16x2 %0, %1, %2, %3;" : "=r"(u) : "r"(u), "r"(v), "r"(0x21622162u));
  return e * 128u + u;
}
constexpr int ATT_SMEM = 2 * HEAD_BYTES + 256;

__device__ __forceinline__ void att_store(const float (&O)[12], int row0, int h, int lane) {
  const float l0 = __shfl_sync(0xffffffffu, O[8], (lane & ~3) | 2), l1 = __shfl_sync(0xffffffffu, O[10], (lane & ~3) | 2);
  const float r0 = __fdividef(1.f, l0), r1 = __fdividef(1.f, l1);
#pragma unroll
  for (int c = 0; c < 3; c++)
    if (c < 2 || (lane & 3) < 2) {
      const int col = h * 20 + c * 8 + (lane & 3) * 2;
      uint32_t* o0 = (uint32_t*)g_o + o_line(row0, col >> 3) * 32 + (row0 & 7) * 4 + ((col & 7) >> 1);
      o0[0] = pack_bf16(O[4 * c] * r0, O[4 * c + 1] * r0);
      o0[256] = pack_bf16(O[4 * c + 2] * r1, O[4 * c + 3] * r1);
    }
}

__global__ void __launch_bounds__(512, 1) att_kernel(const unsigned int* norms, unsigned int* reset_a, unsigned int* reset_b, unsigned int* reset_c, const uint32_t* zeros, int kid) {
  extern __shared__ __align__(1024) uint8_t smem[];
  const uint32_t sK = smem_u32(smem), sV = sK + HEAD_BYTES, bars = sV + HEAD_BYTES + 128;
  const int h = blockIdx.x >> 2, qt = blockIdx.x & 3;
  const int tid = threadIdx.x, lane = tid & 31, wg = __shfl_sync(0xffffffffu, tid >> 7, 0), warp = (tid >> 5) & 3;
  if (tid == 0) {
    for (int c = 0; c < 8; c++) mbar_init(bars + c * 8, 1);
    asm volatile("fence.mbarrier_init.release.cluster;" ::: "memory");
  }
  const uint32_t z0 = __ldg(zeros + (tid & 1)), z1 = __ldg(zeros + 2 + (tid & 1));
  __syncthreads();
  if (tid == 0) TS(kid, 0);
  pdl_wait();
  pdl_launch();
  if (tid == 0) TS(kid, 1);
  const uint8_t* gq = (const uint8_t*)g_qkv + (size_t)h * HEAD_BYTES;
  if (blockIdx.x == 0 && tid < NORM_OFF) { reset_a[tid] = 0u; if (tid < 64) reset_b[tid] = 0u; if (reset_c) reset_c[tid] = 0u; }
  const uint64_t dK = mk_desc(sK, 128, 384, 0);
  const uint64_t dV = mk_desc(sV, 384, 128, 0);
  bool bad = !(__uint_as_float(__ldcg(norms + h)) * __uint_as_float(__ldcg(norms + 32 + h)) <= 3500.f);
  uint32_t q[6];
  auto load_q = [&](int tt) {
    const int row0 = qt * 512 + (tt * 4 + wg) * 64 + warp * 16 + (lane >> 2);
    const uint32_t* qa = (const uint32_t*)(gq + (row0 >> 3) * 384 + (row0 & 7) * 16) + (lane & 3);
    q[0] = __ldcg(qa); q[1] = __ldcg(qa + 96); q[2] = __ldcg(qa + 32); q[3] = __ldcg(qa + 128); q[4] = __ldcg(qa + 64); q[5] = __ldcg(qa + 160);
  };
  load_q(0);
  auto load_kv = [&](int c) {
    const int k0 = c == 0 ? 0 : c * 12288 + 128, k1 = c == 7 ? HEAD_BYTES : (c + 1) * 12288 + 128;
    mbar_expect_tx(bars + c * 8, 12288 + (k1 - k0));
    bulk_g2s(sK + k0, gq + 32 * HEAD_BYTES + k0, k1 - k0, bars + c * 8);
    bulk_g2s(sV + c * 12288, gq + 64 * HEAD_BYTES + c * 12288, 12288, bars + c * 8);
  };
  if (tid == 480) { load_kv(0); load_kv(1); }
  int next_kv = 2;
  if (tid == 0) TS(kid, 6);
  if (!__any_sync(0xffffffffu, bad)) {
  if (tid == 0) TS(kid, 7);
  if (tid == 0 && (q[0] ^ q[1] ^ q[2] ^ q[3] ^ q[4] ^ q[5]) != 0x12345u) TS(kid, 24);
#pragma unroll 1
  for (int tt = 0; tt < 2; tt++) {
    const int row0 = qt * 512 + (tt * 4 + wg) * 64 + warp * 16 + (lane >> 2);
    float S[64], O[12];
    uint32_t P[32];
#pragma unroll
    for (int k = 0; k < 12; k++) O[k] = 0.f;
#pragma unroll
    for (int k = 0; k < 64; k++) S[k] = 0.f;
    uint64_t gk = dK, gv = dV;
#pragma unroll 1
    for (int g = 0; g < 16; g++) {
      if (tid == 0 && tt == 0 && g < 1) TS(kid, 8 + g * 2);
      if ((g & 1) == 0) {
        if (next_kv < 8) { if (tid == 480) load_kv(next_kv); next_kv++; }
        mbar_wait(bars + (g >> 1) * 8, 0);
      }
      if (tid == 0 && tt == 0 && g < 1) TS(kid, 9 + g * 2);
      wg_fence();
      wgmma_rs_n128<0>(S, q[0], q[1], q[2], q[3], gk, 0);
      wgmma_rs_n128<0>(S, q[4], q[5], z0, z1, gk + 16, 1);
      wg_commit();
      wg_wait<0>();
      fence_regs(S);
#pragma unroll
      for (int b = 0; b < 16; b++) {
        if (is_mufu(b)) { P[2 * b] = pack_bf16(ex2(S[4 * b]), ex2(S[4 * b + 1])); P[2 * b + 1] = pack_bf16(ex2(S[4 * b + 2]), ex2(S[4 * b + 3])); }
        else { P[2 * b] = exp2_poly_pair(S[4 * b], S[4 * b + 1]); P[2 * b + 1] = exp2_poly_pair(S[4 * b + 2], S[4 * b + 3]); }
      }
      fence_regs(P);
      wg_fence();
#pragma unroll
      for (int s = 0; s < 8; s++) wgmma_rs_n24<1>(O, P[4 * s], P[4 * s + 1], P[4 * s + 2], P[4 * s + 3], gv + s * 48, 1);
      wg_commit();
      wg_wait<0>();
      gk += 384; gv += 384;
    }
    fence_regs(O);
    if (tid == 0) TS(kid, 2 + tt);
    load_q(1);
    att_store(O, row0, h, lane);
    float m = 0.f;
#pragma unroll
    for (int k = 0; k < 12; k++) { m = fmaxf(m, fabsf(O[k])); bad |= (O[k] != O[k]); }
    bad |= !(m <= 3e38f);
    if ((lane & 3) == 2) bad |= !(O[8] >= 0x1p-20f) || !(O[10] >= 0x1p-20f);
  }
  }
  if (tid == 0) TS(kid, 4);
  if (__syncthreads_or(bad)) {
    if (tid == 0) TS(kid, 5);
    if (tid == 480)
      for (; next_kv < 8; next_kv++) load_kv(next_kv);
    for (int c = 0; c < 8; c++) mbar_wait(bars + c * 8, 0);
#pragma unroll 1
    for (int tt = 0; tt < 2; tt++) {
      const int row0 = qt * 512 + (tt * 4 + wg) * 64 + warp * 16 + (lane >> 2);
      load_q(tt);
      if ((lane & 3) >= 2) { q[4] = 0u; q[5] = 0u; }
      float S[64], O[12], m0 = -INFINITY, m1 = -INFINITY;
      uint32_t P[32];
#pragma unroll
      for (int k = 0; k < 12; k++) O[k] = 0.f;
#pragma unroll
      for (int k = 0; k < 64; k++) S[k] = 0.f;
      uint64_t gk = dK, gv = dV;
#pragma unroll 1
      for (int g = 0; g < 16; g++) {
        wg_fence();
        wgmma_rs_n128<0>(S, q[0], q[1], q[2], q[3], gk, 0);
        wgmma_rs_n128<0>(S, q[4], q[5], z0, z1, gk + 16, 1);
        wg_commit();
        wg_wait<0>();
        fence_regs(S);
        float x0 = m0, x1 = m1;
#pragma unroll
        for (int b = 0; b < 16; b++) {
          if (!is_mufu(b)) { S[4 * b] *= 0x1p22f; S[4 * b + 1] *= 0x1p22f; S[4 * b + 2] *= 0x1p22f; S[4 * b + 3] *= 0x1p22f; }
          x0 = fmaxf(x0, fmaxf(S[4 * b], S[4 * b + 1]));
          x1 = fmaxf(x1, fmaxf(S[4 * b + 2], S[4 * b + 3]));
        }
        x0 = fmaxf(x0, __shfl_xor_sync(0xffffffffu, x0, 1)); x1 = fmaxf(x1, __shfl_xor_sync(0xffffffffu, x1, 1));
        x0 = fmaxf(x0, __shfl_xor_sync(0xffffffffu, x0, 2)); x1 = fmaxf(x1, __shfl_xor_sync(0xffffffffu, x1, 2));
        const float al0 = ex2(m0 - x0), al1 = ex2(m1 - x1);
        m0 = x0; m1 = x1;
#pragma unroll
        for (int c = 0; c < 3; c++) { O[4 * c] *= al0; O[4 * c + 1] *= al0; O[4 * c + 2] *= al1; O[4 * c + 3] *= al1; }
#pragma unroll
        for (int b = 0; b < 16; b++) {
          P[2 * b] = pack_bf16(ex2(S[4 * b] - m0), ex2(S[4 * b + 1] - m0));
          P[2 * b + 1] = pack_bf16(ex2(S[4 * b + 2] - m1), ex2(S[4 * b + 3] - m1));
        }
        fence_regs(P);
        fence_regs(O);
        wg_fence();
#pragma unroll
        for (int s = 0; s < 8; s++) wgmma_rs_n24<1>(O, P[4 * s], P[4 * s + 1], P[4 * s + 2], P[4 * s + 3], gv + s * 48, 1);
        wg_commit();
        wg_wait<0>();
        fence_regs(O);
        gk += 384; gv += 384;
      }
      att_store(O, row0, h, lane);
    }
  }
}

typedef CUresult (*EncodeFn)(CUtensorMap*, CUtensorMapDataType, cuuint32_t, void*, const cuuint64_t*, const cuuint64_t*, const cuuint32_t*,
                             const cuuint32_t*, CUtensorMapInterleave, CUtensorMapSwizzle, CUtensorMapL2promotion, CUtensorMapFloatOOBfill);

static void make_a(EncodeFn enc, CUtensorMap* m, const void* ptr, int K) {
  cuuint64_t dims[2] = {(cuuint64_t)K, (cuuint64_t)SEQ}, strides[1] = {(cuuint64_t)K * 2};
  cuuint32_t box[2] = {64, 128}, es[2] = {1, 1};
  enc(m, CU_TENSOR_MAP_DATA_TYPE_BFLOAT16, 2, (void*)ptr, dims, strides, box, es, CU_TENSOR_MAP_INTERLEAVE_NONE, CU_TENSOR_MAP_SWIZZLE_128B,
      CU_TENSOR_MAP_L2_PROMOTION_NONE, CU_TENSOR_MAP_FLOAT_OOB_FILL_NONE);
}
static void make_out(EncodeFn enc, CUtensorMap* m, void* ptr) {
  cuuint64_t dims[2] = {(cuuint64_t)DM, (cuuint64_t)SEQ}, strides[1] = {(cuuint64_t)DM * 2};
  cuuint32_t box[2] = {160, 64}, es[2] = {1, 1};
  enc(m, CU_TENSOR_MAP_DATA_TYPE_BFLOAT16, 2, ptr, dims, strides, box, es, CU_TENSOR_MAP_INTERLEAVE_NONE, CU_TENSOR_MAP_SWIZZLE_NONE,
      CU_TENSOR_MAP_L2_PROMOTION_NONE, CU_TENSOR_MAP_FLOAT_OOB_FILL_NONE);
}
static void make_b(EncodeFn enc, CUtensorMap* m, const void* ptr, int K, int N, int BN, int bk, int bw) {
  cuuint64_t dims[3] = {(cuuint64_t)BN, (cuuint64_t)(N / BN), (cuuint64_t)K}, strides[2] = {(cuuint64_t)BN * 2, (cuuint64_t)N * 2};
  cuuint32_t box[3] = {(cuuint32_t)bw, 1, (cuuint32_t)bk}, es[3] = {1, 1, 1};
  enc(m, CU_TENSOR_MAP_DATA_TYPE_BFLOAT16, 3, (void*)ptr, dims, strides, box, es, CU_TENSOR_MAP_INTERLEAVE_NONE, bw == 64 ? CU_TENSOR_MAP_SWIZZLE_128B : CU_TENSOR_MAP_SWIZZLE_64B,
      CU_TENSOR_MAP_L2_PROMOTION_NONE, CU_TENSOR_MAP_FLOAT_OOB_FILL_NONE);
}
template <typename... KArgs, typename... Args>
static void launch(void (*kern)(KArgs...), int grid, int threads, int smem, bool pdl, Args... args) {
  cudaFuncSetAttribute(kern, cudaFuncAttributeMaxDynamicSharedMemorySize, smem);
  cudaLaunchConfig_t cfg = {};
  cfg.gridDim = dim3(grid); cfg.blockDim = dim3(threads); cfg.dynamicSmemBytes = smem; cfg.stream = cudaStreamPerThread;
  cudaLaunchAttribute at[1];
  at[0].id = cudaLaunchAttributeProgrammaticStreamSerialization; at[0].val.programmaticStreamSerializationAllowed = 1;
  cfg.attrs = at; cfg.numAttrs = pdl ? 1 : 0;
  cudaLaunchKernelEx(&cfg, kern, KArgs(args)...);
}

static void make_pref(signed char* pref, int ntpc) {
  auto kern = chain_kernel<PH_WO | PH_W1 | PH_W2, false, true>;
  cudaFuncSetAttribute(kern, cudaFuncAttributeMaxDynamicSharedMemorySize, CHAIN_SMEM);
  cudaFuncSetAttribute(kern, cudaFuncAttributeNonPortableClusterSizeAllowed, 1);
  int n[10] = {0};
  for (int t = 2; t <= 8; t++) {
    cudaLaunchConfig_t cfg = {};
    cfg.gridDim = dim3(2 * t * 16); cfg.blockDim = dim3(CHAIN_THREADS); cfg.dynamicSmemBytes = CHAIN_SMEM;
    cudaLaunchAttribute at[1];
    at[0].id = cudaLaunchAttributeClusterDimension; at[0].val.clusterDim.x = 2 * t; at[0].val.clusterDim.y = 1; at[0].val.clusterDim.z = 1;
    cfg.attrs = at; cfg.numAttrs = 1;
    if (cudaOccupancyMaxActiveClusters(&n[t], kern, &cfg) != cudaSuccess) { n[t] = -1; cudaGetLastError(); }
  }
  int best[10] = {0}, cnt[10], found = 0;
  for (int code = 0; code < 1000000 && !found; code++) {
    int c = code, tot = 0, g = 0;
    for (int m = 0; m < 10; m++) cnt[m] = 0;
    for (int m = 4; m <= 9; m++) { cnt[m] = c % 10; c /= 10; tot += cnt[m] * m; g += cnt[m]; }
    if (g > 9 || tot > ntpc) continue;
    bool ok = true;
    for (int t = 3; t <= 8 && ok; t++) { int s = 0; for (int m = 4; m <= 9; m++) s += cnt[m] * (m / t); ok = (s == n[t]); }
    if (ok) { found = 1; for (int m = 0; m < 10; m++) best[m] = cnt[m]; }
  }
  int grp[80], size[10], ng = 0, id = 0;
  for (int t = 0; t < 80; t++) { grp[t] = -1; pref[2 * t] = pref[2 * t + 1] = -1; }
  if (found) {
    for (int m = 4; m <= 9; m++) for (int k = 0; k < best[m]; k++) size[ng++] = m;
    for (int r = 0; r < 9; r++) for (int g = 0; g < ng; g++) if (size[g] > r && id < ntpc) grp[id++] = g;
  }
  int nb = 0;
  bool used[80] = {false};
  auto put = [&](int t, int blk, int w) {
    const int tile = ((blk >> 1) * 4 + (w >> 1)) * 8 + (blk & 1) * 4 + (w & 1) * 2;
    pref[2 * t] = (signed char)tile; pref[2 * t + 1] = (signed char)(tile + 1); used[t] = true;
  };
  for (int g = 0; g < ng && nb < 8; g++)
    if (size[g] >= 8) {
      int w = 0;
      for (int t = 0; t < ntpc && w < 8; t++) if (grp[t] == g) put(t, nb, w++);
      nb++;
    }
  int pos = nb * 8;
  for (int pass = 0; pass < 2; pass++)
    for (int g = 0; g <= ng; g++)
      for (int t = 0; t < ntpc && pos < 64; t++)
        if (!used[t] && (g < ng ? (grp[t] == g && (size[g] < 8) == (pass == 0)) : (pass == 1 && grp[t] < 0))) { put(t, pos >> 3, pos & 7); pos++; }
}

extern "C" void kernel_launch(void* const* d_in, const int* in_sizes, int n_in, void* d_out, int out_size) {
  const bf16* x = (const bf16*)d_in[0];
  const bf16* wqkv = (const bf16*)d_in[1];
  const bf16* wo = (const bf16*)d_in[2];
  const bf16* w1 = (const bf16*)d_in[4];
  const bf16* b1 = (const bf16*)d_in[5];
  const bf16* w2 = (const bf16*)d_in[6];
  const bf16* b2 = (const bf16*)d_in[7];
  void* fn = nullptr;
  cudaDriverEntryPointQueryResult qr;
  cudaGetDriverEntryPoint("cuTensorMapEncodeTiled", &fn, cudaEnableDefault, &qr);
  EncodeFn enc = (EncodeFn)fn;
  void *px0, *px2, *pf, *pz;
  cudaGetSymbolAddress(&px0, g_x0);
  cudaGetSymbolAddress(&px2, g_x2); cudaGetSymbolAddress(&pf, g_s);
  unsigned int* flags = ((Small*)pf)->flags;
  pz = ((Small*)pf)->zeros;

  int nsm = 132;
  cudaDeviceGetAttribute(&nsm, cudaDevAttrMultiProcessorCount, 0);
  const int ngrid = nsm >= 128 ? (nsm > 160 ? 160 : (nsm & ~1)) : 128;
  ChainParams p;
  make_pref(p.pref, ngrid / 2);
  make_a(enc, &p.a_x, x, DM);
  make_out(enc, &p.o_out, d_out);
  make_b(enc, &p.b_wo, wo, DM, DM, 160, 64, 32); make_b(enc, &p.b_w1, w1, DM, FF, 216, 64, 32); make_b(enc, &p.b_w2, w2, FF, DM, 160, 96, 32);
  make_b(enc, &p.b_wqkv, wqkv, DM, 1920, 240, 64, 64);
  p.xres = (const bf16*)px0; p.xin = x; p.b1 = b1; p.b2 = b2; p.flags = flags; p.kid = 0;

  launch(chain_kernel<PH_QKV, true, false>, ngrid, FIRST_THREADS, CHAIN_SMEM, false, p);
  launch(att_kernel, 128, 512, ATT_SMEM, true, flags + NORM_OFF, flags, flags + FLAG_SET + NORM_OFF, flags + 2 * FLAG_SET, (const uint32_t*)pz, 1);
  p.flags = flags + FLAG_SET; p.kid = 2;
  launch(chain_kernel<PH_WO | PH_W1 | PH_W2 | PH_QKV, false, false>, ngrid, CHAIN_THREADS, CHAIN_SMEM, true, p);
  launch(att_kernel, 128, 512, ATT_SMEM, true, flags + FLAG_SET + NORM_OFF, flags + FLAG_SET, flags + NORM_OFF, (unsigned int*)nullptr, (const uint32_t*)pz, 3);
  p.kid = 4; p.xres = (const bf16*)px2; p.flags = flags + 2 * FLAG_SET;
  launch(chain_kernel<PH_WO | PH_W1 | PH_W2, false, true>, ngrid, CHAIN_THREADS, CHAIN_SMEM, true, p);
}
```

```cpp
#include <cuda_runtime.h>
#include <cuda_bf16.h>
#include <cuda.h>
#include <stdint.h>

#define BL1 2
#define BL2 2
#define BL3 2
#define KLIM 4
#define MUFUM 0x1249u
typedef __nv_bfloat16 bf16;

constexpr int SEQ = 2048, DM = 640, FF = 1728;
constexpr float LN_EPS = 1e-5f;
constexpr int HEAD_BYTES = 98304;
constexpr uint32_t MUFU_MASK = MUFUM;
__host__ __device__ constexpr bool is_mufu(int g) { return (MUFU_MASK >> (g & 15)) & 1u; }

__device__ __align__(1024) bf16 g_qkv[96 * (HEAD_BYTES / 2)];
constexpr int WT_WO = 0, WT_W1 = WT_WO + 80 * 10240, WT_W2 = WT_W1 + 160 * 14336, WT_QKV = WT_W2 + 144 * 15360, WT_END = WT_QKV + 160 * 16384;
__device__ __align__(1024) uint8_t g_wt[WT_END];
__device__ __forceinline__ int x_line(int row, int cg) { return (((row >> 7) * 10 + (cg >> 3)) * 16 + ((row >> 3) & 15)) * 8 + (cg & 7); }
__device__ __forceinline__ int o_line(int row, int cg) { return (((row >> 6) * 10 + (cg >> 3)) * 8 + ((row >> 3) & 7)) * 8 + (cg & 7); }
__device__ __forceinline__ int h_line(int row, int cg) { return (((row >> 6) * 18 + cg / 12) * 8 + ((row >> 3) & 7)) * 12 + cg % 12; }
__device__ __align__(1024) bf16 g_x0[SEQ * DM];
__device__ __align__(1024) bf16 g_o[SEQ * DM];
__device__ __align__(1024) bf16 g_x1[SEQ * DM];
__device__ __align__(1024) bf16 g_x2[SEQ * DM];
__device__ __align__(1024) bf16 g_h[SEQ * FF];
constexpr int FLAG_SET = 320, NORM_OFF = 256;
struct Small {
  float2 st0[2 * SEQ];
  float2 st1[8 * SEQ];
  float2 st2[8 * SEQ];
  float csp_w1[10 * 1792];
  float cs_qkv[1920];
  unsigned int flags[3 * FLAG_SET];
  uint32_t zeros[4];
};
__device__ __align__(1024) Small g_s;

#define TS(k, s) do {} while (0)
#define DBG(x)
__device__ __forceinline__ uint32_t smem_u32(const void* p) { return (uint32_t)__cvta_generic_to_shared(p); }
__device__ __forceinline__ void mbar_init(uint32_t bar, int cnt) { asm volatile("mbarrier.init.shared::cta.b64 [%0], %1;" ::"r"(bar), "r"(cnt) : "memory"); }
__device__ __forceinline__ void mbar_expect_tx(uint32_t bar, uint32_t bytes) { asm volatile("mbarrier.arrive.expect_tx.shared::cta.b64 _, [%0], %1;" ::"r"(bar), "r"(bytes) : "memory"); }
__device__ __forceinline__ void mbar_arrive(uint32_t bar) { asm volatile("mbarrier.arrive.shared::cta.b64 _, [%0];" ::"r"(bar) : "memory"); }
__device__ __forceinline__ bool mbar_try(uint32_t bar, uint32_t parity) {
  uint32_t ok;
  asm volatile("{\n.reg .pred p;\nmbarrier.try_wait.parity.shared::cta.b64 p, [%1], %2;\nselp.u32 %0, 1, 0, p;\n}\n" : "=r"(ok) : "r"(bar), "r"(parity) : "memory");
  return ok != 0;
}
__device__ __forceinline__ bool mbar_test(uint32_t bar, uint32_t parity) {
  uint32_t ok;
  asm volatile("{\n.reg .pred p;\nmbarrier.test_wait.parity.shared::cta.b64 p, [%1], %2;\nselp.u32 %0, 1, 0, p;\n}\n" : "=r"(ok) : "r"(bar), "r"(parity) : "memory");
  return ok != 0;
}
__device__ __forceinline__ void mbar_wait(uint32_t bar, uint32_t parity) {
  if (mbar_try(bar, parity)) return;
#pragma unroll 1
  for (int it = 0; it < (1 << 22); it++)
    if (mbar_try(bar, parity)) return;
  __trap();
}
__device__ __forceinline__ void flag_wait(const unsigned int* f, unsigned int target) {
  unsigned int v;
#pragma unroll 1
  for (int it = 0; it < (1 << 22); it++) {
    asm volatile("ld.acquire.gpu.global.u32 %0, [%1];" : "=r"(v) : "l"(f) : "memory");
    if (v >= target) return;
  }
  __trap();
}
__device__ __forceinline__ void flag_signal(unsigned int* f) { asm volatile("red.release.gpu.global.add.u32 [%0], 1;" ::"l"(f) : "memory"); }
__device__ __forceinline__ void fence_async_global() { asm volatile("fence.proxy.async.global;" ::: "memory"); }
__device__ __forceinline__ void pdl_wait() { asm volatile("griddepcontrol.wait;" ::: "memory"); }
__device__ __forceinline__ void pdl_launch() { asm volatile("griddepcontrol.launch_dependents;" ::: "memory"); }
__device__ __forceinline__ void named_bar(int id, int n) { asm volatile("bar.sync %0, %1;" ::"r"(id), "r"(n) : "memory"); }
__device__ __forceinline__ void bulk_g2s(uint32_t dst, const void* src, uint32_t bytes, uint32_t bar) {
  asm volatile("cp.async.bulk.shared::cluster.global.mbarrier::complete_tx::bytes [%0], [%1], %2, [%3];" ::"r"(dst), "l"(src), "r"(bytes), "r"(bar) : "memory");
}
__device__ __forceinline__ void prefetch_l2(const void* src, uint32_t bytes) { asm volatile("cp.async.bulk.prefetch.L2.global [%0], %1;" ::"l"(src), "r"(bytes) : "memory"); }
__device__ __forceinline__ void tma_2d(uint32_t dst, const CUtensorMap* m, int c0, int c1, uint32_t bar) {
  asm volatile("cp.async.bulk.tensor.2d.shared::cluster.global.mbarrier::complete_tx::bytes [%0], [%1, {%3, %4}], [%2];" ::"r"(dst), "l"(m), "r"(bar), "r"(c0), "r"(c1) : "memory");
}
__device__ __forceinline__ void tma_3d(uint32_t dst, const CUtensorMap* m, int c0, int c1, int c2, uint32_t bar) {
  asm volatile("cp.async.bulk.tensor.3d.shared::cluster.global.mbarrier::complete_tx::bytes [%0], [%1, {%3, %4, %5}], [%2];" ::"r"(dst), "l"(m), "r"(bar), "r"(c0), "r"(c1), "r"(c2) : "memory");
}
__device__ __forceinline__ void prefetch_map(const CUtensorMap* m) { asm volatile("prefetch.tensormap [%0];" ::"l"(m) : "memory"); }
__device__ __forceinline__ void wg_fence() { asm volatile("wgmma.fence.sync.aligned;" ::: "memory"); }
__device__ __forceinline__ void wg_commit() { asm volatile("wgmma.commit_group.sync.aligned;" ::: "memory"); }
template <int N> __device__ __forceinline__ void wg_wait() { asm volatile("wgmma.wait_group.sync.aligned %0;" ::"n"(N) : "memory"); }
template <int N> __device__ __forceinline__ void fence_regs(float (&d)[N]) {
#pragma unroll
  for (int i = 0; i < N; i++) asm volatile("" : "+f"(d[i])::"memory");
}
template <int N> __device__ __forceinline__ void fence_regs(uint32_t (&d)[N]) {
#pragma unroll
  for (int i = 0; i < N; i++) asm volatile("" : "+r"(d[i])::"memory");
}
__device__ __forceinline__ uint64_t mk_desc(uint32_t addr, uint32_t lbo, uint32_t sbo, uint64_t swz) {
  return (uint64_t)((addr & 0x3FFFF) >> 4) | ((uint64_t)(lbo >> 4) << 16) | ((uint64_t)(sbo >> 4) << 32) | (swz << 62);
}
__device__ __forceinline__ uint32_t pack_bf16(float lo, float hi) {
  uint32_t r;
  asm("cvt.rn.bf16x2.f32 %0, %1, %2;" : "=r"(r) : "f"(hi), "f"(lo));
  return r;
}
__device__ __forceinline__ float bf_lo(uint32_t v) { return __uint_as_float(v << 16); }
__device__ __forceinline__ float bf_hi(uint32_t v) { return __uint_as_float(v & 0xFFFF0000u); }
__device__ __forceinline__ float ex2(float x) { float r; asm("ex2.approx.ftz.f32 %0, %1;" : "=f"(r) : "f"(x)); return r; }

template<int TB> __device__ __forceinline__ void wgmma_rs_n24(float (&d)[12], uint32_t a0, uint32_t a1, uint32_t a2, uint32_t a3, uint64_t db, int sd) {
  asm volatile("{\n.reg .pred p;\nsetp.ne.b32 p, %17, 0;\n"
    "wgmma.mma_async.sync.aligned.m64n24k16.f32.bf16.bf16 "
    "{%0,%1,%2,%3,%4,%5,%6,%7,%8,%9,%10,%11}, "
    "{%12,%13,%14,%15}, %16, p, 1, 1, %18;\n}\n"
    : "+f"(d[0]),"+f"(d[1]),"+f"(d[2]),"+f"(d[3]),"+f"(d[4]),"+f"(d[5]),"+f"(d[6]),"+f"(d[7]),"+f"(d[8]),"+f"(d[9]),"+f"(d[10]),"+f"(d[11])
    : "r"(a0), "r"(a1), "r"(a2), "r"(a3), "l"(db), "r"(sd), "n"(TB));
}
template<int TB> __device__ __forceinline__ void wgmma_rs_n120(float (&d)[60], uint32_t a0, uint32_t a1, uint32_t a2, uint32_t a3, uint64_t db, int sd) {
  asm volatile("{\n.reg .pred p;\nsetp.ne.b32 p, %65, 0;\n"
    "wgmma.mma_async.sync.aligned.m64n120k16.f32.bf16.bf16 "
    "{%0,%1,%2,%3,%4,%5,%6,%7,%8,%9,%10,%11,%12,%13,%14,%15,%16,%17,%18,%19,%20,%21,%22,%23,%24,%25,%26,%27,%28,%29,%30,%31,%32,%33,%34,%35,%36,%37,%38,%39,%40,%41,%42,%43,%44,%45,%46,%47,%48,%49,%50,%51,%52,%53,%54,%55,%56,%57,%58,%59}, "
    "{%60,%61,%62,%63}, %64, p, 1, 1, %66;\n}\n"
    : "+f"(d[0]),"+f"(d[1]),"+f"(d[2]),"+f"(d[3]),"+f"(d[4]),"+f"(d[5]),"+f"(d[6]),"+f"(d[7]),"+f"(d[8]),"+f"(d[9]),"+f"(d[10]),"+f"(d[11]),"+f"(d[12]),"+f"(d[13]),"+f"(d[14]),"+f"(d[15]),"+f"(d[16]),"+f"(d[17]),"+f"(d[18]),"+f"(d[19]),"+f"(d[20]),"+f"(d[21]),"+f"(d[22]),"+f"(d[23]),"+f"(d[24]),"+f"(d[25]),"+f"(d[26]),"+f"(d[27]),"+f"(d[28]),"+f"(d[29]),"+f"(d[30]),"+f"(d[31]),"+f"(d[32]),"+f"(d[33]),"+f"(d[34]),"+f"(d[35]),"+f"(d[36]),"+f"(d[37]),"+f"(d[38]),"+f"(d[39]),"+f"(d[40]),"+f"(d[41]),"+f"(d[42]),"+f"(d[43]),"+f"(d[44]),"+f"(d[45]),"+f"(d[46]),"+f"(d[47]),"+f"(d[48]),"+f"(d[49]),"+f"(d[50]),"+f"(d[51]),"+f"(d[52]),"+f"(d[53]),"+f"(d[54]),"+f"(d[55]),"+f"(d[56]),"+f"(d[57]),"+f"(d[58]),"+f"(d[59])
    : "r"(a0), "r"(a1), "r"(a2), "r"(a3), "l"(db), "r"(sd), "n"(TB));
}
template<int TB> __device__ __forceinline__ void wgmma_rs_n128(float (&d)[64], uint32_t a0, uint32_t a1, uint32_t a2, uint32_t a3, uint64_t db, int sd) {
  asm volatile("{\n.reg .pred p;\nsetp.ne.b32 p, %69, 0;\n"
    "wgmma.mma_async.sync.aligned.m64n128k16.f32.bf16.bf16 "
    "{%0,%1,%2,%3,%4,%5,%6,%7,%8,%9,%10,%11,%12,%13,%14,%15,%16,%17,%18,%19,%20,%21,%22,%23,%24,%25,%26,%27,%28,%29,%30,%31,%32,%33,%34,%35,%36,%37,%38,%39,%40,%41,%42,%43,%44,%45,%46,%47,%48,%49,%50,%51,%52,%53,%54,%55,%56,%57,%58,%59,%60,%61,%62,%63}, "
    "{%64,%65,%66,%67}, %68, p, 1, 1, %70;\n}\n"
    : "+f"(d[0]),"+f"(d[1]),"+f"(d[2]),"+f"(d[3]),"+f"(d[4]),"+f"(d[5]),"+f"(d[6]),"+f"(d[7]),"+f"(d[8]),"+f"(d[9]),"+f"(d[10]),"+f"(d[11]),"+f"(d[12]),"+f"(d[13]),"+f"(d[14]),"+f"(d[15]),"+f"(d[16]),"+f"(d[17]),"+f"(d[18]),"+f"(d[19]),"+f"(d[20]),"+f"(d[21]),"+f"(d[22]),"+f"(d[23]),"+f"(d[24]),"+f"(d[25]),"+f"(d[26]),"+f"(d[27]),"+f"(d[28]),"+f"(d[29]),"+f"(d[30]),"+f"(d[31]),"+f"(d[32]),"+f"(d[33]),"+f"(d[34]),"+f"(d[35]),"+f"(d[36]),"+f"(d[37]),"+f"(d[38]),"+f"(d[39]),"+f"(d[40]),"+f"(d[41]),"+f"(d[42]),"+f"(d[43]),"+f"(d[44]),"+f"(d[45]),"+f"(d[46]),"+f"(d[47]),"+f"(d[48]),"+f"(d[49]),"+f"(d[50]),"+f"(d[51]),"+f"(d[52]),"+f"(d[53]),"+f"(d[54]),"+f"(d[55]),"+f"(d[56]),"+f"(d[57]),"+f"(d[58]),"+f"(d[59]),"+f"(d[60]),"+f"(d[61]),"+f"(d[62]),"+f"(d[63])
    : "r"(a0), "r"(a1), "r"(a2), "r"(a3), "l"(db), "r"(sd), "n"(TB));
}
__device__ __forceinline__ void wgmma_ss(float (&d)[40], uint64_t da, uint64_t db, int sd) {
  asm volatile("{\n.reg .pred p;\nsetp.ne.b32 p, %42, 0;\n"
    "wgmma.mma_async.sync.aligned.m64n80k16.f32.bf16.bf16 "
    "{%0,%1,%2,%3,%4,%5,%6,%7,%8,%9,%10,%11,%12,%13,%14,%15,%16,%17,%18,%19,%20,%21,%22,%23,%24,%25,%26,%27,%28,%29,%30,%31,%32,%33,%34,%35,%36,%37,%38,%39}, "
    "%40, %41, p, 1, 1, 0, 1;\n}\n"
    : "+f"(d[0]),"+f"(d[1]),"+f"(d[2]),"+f"(d[3]),"+f"(d[4]),"+f"(d[5]),"+f"(d[6]),"+f"(d[7]),"+f"(d[8]),"+f"(d[9]),"+f"(d[10]),"+f"(d[11]),"+f"(d[12]),"+f"(d[13]),"+f"(d[14]),"+f"(d[15]),"+f"(d[16]),"+f"(d[17]),"+f"(d[18]),"+f"(d[19]),"+f"(d[20]),"+f"(d[21]),"+f"(d[22]),"+f"(d[23]),"+f"(d[24]),"+f"(d[25]),"+f"(d[26]),"+f"(d[27]),"+f"(d[28]),"+f"(d[29]),"+f"(d[30]),"+f"(d[31]),"+f"(d[32]),"+f"(d[33]),"+f"(d[34]),"+f"(d[35]),"+f"(d[36]),"+f"(d[37]),"+f"(d[38]),"+f"(d[39])
    : "l"(da), "l"(db), "r"(sd));
}
__device__ __forceinline__ void wgmma_ss(float (&d)[56], uint64_t da, uint64_t db, int sd) {
  asm volatile("{\n.reg .pred p;\nsetp.ne.b32 p, %58, 0;\n"
    "wgmma.mma_async.sync.aligned.m64n112k16.f32.bf16.bf16 "
    "{%0,%1,%2,%3,%4,%5,%6,%7,%8,%9,%10,%11,%12,%13,%14,%15,%16,%17,%18,%19,%20,%21,%22,%23,%24,%25,%26,%27,%28,%29,%30,%31,%32,%33,%34,%35,%36,%37,%38,%39,%40,%41,%42,%43,%44,%45,%46,%47,%48,%49,%50,%51,%52,%53,%54,%55}, "
    "%56, %57, p, 1, 1, 0, 1;\n}\n"
    : "+f"(d[0]),"+f"(d[1]),"+f"(d[2]),"+f"(d[3]),"+f"(d[4]),"+f"(d[5]),"+f"(d[6]),"+f"(d[7]),"+f"(d[8]),"+f"(d[9]),"+f"(d[10]),"+f"(d[11]),"+f"(d[12]),"+f"(d[13]),"+f"(d[14]),"+f"(d[15]),"+f"(d[16]),"+f"(d[17]),"+f"(d[18]),"+f"(d[19]),"+f"(d[20]),"+f"(d[21]),"+f"(d[22]),"+f"(d[23]),"+f"(d[24]),"+f"(d[25]),"+f"(d[26]),"+f"(d[27]),"+f"(d[28]),"+f"(d[29]),"+f"(d[30]),"+f"(d[31]),"+f"(d[32]),"+f"(d[33]),"+f"(d[34]),"+f"(d[35]),"+f"(d[36]),"+f"(d[37]),"+f"(d[38]),"+f"(d[39]),"+f"(d[40]),"+f"(d[41]),"+f"(d[42]),"+f"(d[43]),"+f"(d[44]),"+f"(d[45]),"+f"(d[46]),"+f"(d[47]),"+f"(d[48]),"+f"(d[49]),"+f"(d[50]),"+f"(d[51]),"+f"(d[52]),"+f"(d[53]),"+f"(d[54]),"+f"(d[55])
    : "l"(da), "l"(db), "r"(sd));
}
__device__ __forceinline__ void wgmma_ss(float (&d)[60], uint64_t da, uint64_t db, int sd) {
  asm volatile("{\n.reg .pred p;\nsetp.ne.b32 p, %62, 0;\n"
    "wgmma.mma_async.sync.aligned.m64n120k16.f32.bf16.bf16 "
    "{%0,%1,%2,%3,%4,%5,%6,%7,%8,%9,%10,%11,%12,%13,%14,%15,%16,%17,%18,%19,%20,%21,%22,%23,%24,%25,%26,%27,%28,%29,%30,%31,%32,%33,%34,%35,%36,%37,%38,%39,%40,%41,%42,%43,%44,%45,%46,%47,%48,%49,%50,%51,%52,%53,%54,%55,%56,%57,%58,%59}, "
    "%60, %61, p, 1, 1, 0, 1;\n}\n"
    : "+f"(d[0]),"+f"(d[1]),"+f"(d[2]),"+f"(d[3]),"+f"(d[4]),"+f"(d[5]),"+f"(d[6]),"+f"(d[7]),"+f"(d[8]),"+f"(d[9]),"+f"(d[10]),"+f"(d[11]),"+f"(d[12]),"+f"(d[13]),"+f"(d[14]),"+f"(d[15]),"+f"(d[16]),"+f"(d[17]),"+f"(d[18]),"+f"(d[19]),"+f"(d[20]),"+f"(d[21]),"+f"(d[22]),"+f"(d[23]),"+f"(d[24]),"+f"(d[25]),"+f"(d[26]),"+f"(d[27]),"+f"(d[28]),"+f"(d[29]),"+f"(d[30]),"+f"(d[31]),"+f"(d[32]),"+f"(d[33]),"+f"(d[34]),"+f"(d[35]),"+f"(d[36]),"+f"(d[37]),"+f"(d[38]),"+f"(d[39]),"+f"(d[40]),"+f"(d[41]),"+f"(d[42]),"+f"(d[43]),"+f"(d[44]),"+f"(d[45]),"+f"(d[46]),"+f"(d[47]),"+f"(d[48]),"+f"(d[49]),"+f"(d[50]),"+f"(d[51]),"+f"(d[52]),"+f"(d[53]),"+f"(d[54]),"+f"(d[55]),"+f"(d[56]),"+f"(d[57]),"+f"(d[58]),"+f"(d[59])
    : "l"(da), "l"(db), "r"(sd));
}

constexpr int PH_WO = 1, PH_W1 = 2, PH_W2 = 4, PH_QKV = 8;
constexpr int SA = 4, SB = 10, STAGE = 16384;
constexpr int SM_B = SA * STAGE;
constexpr int SM_CS = SM_B + SB * STAGE;
constexpr int SM_B1 = SM_CS + 448;
constexpr int SM_ROW = SM_B1 + 224;
constexpr int SM_BAR = SM_ROW + 2048;
constexpr int CHAIN_SMEM = SM_BAR + 344;
static_assert(CHAIN_SMEM <= 232448, "shared memory");
constexpr int CHAIN_THREADS = 352;
constexpr int BAR_FA = 0, BAR_EA = SA * 8, BAR_FB = 2 * SA * 8, BAR_EB = (2 * SA + SB) * 8, BAR_AUX = (2 * SA + 2 * SB) * 8, BAR_JOB = BAR_AUX + 32,
              BAR_FH = BAR_JOB, BAR_EH = BAR_JOB + 40, BAR_TILE = BAR_JOB + 80;

struct alignas(64) ChainParams {
  CUtensorMap a_x, b_wo, b_w1, b_w2, b_wqkv, o_out;
  const bf16* xres;
  const bf16* xin;
  const bf16 *b1, *b2;
  unsigned int* flags;
  int kid;
  signed char pref[160];
};

struct Ring { uint32_t s, ph; };
template <int N> __device__ __forceinline__ void ring_adv(Ring& r) { if (++r.s == N) { r.s = 0; r.ph ^= 1; } }

template <int KT, int BYTES, int N, int STRIDE = STAGE, int LIM = 0>
__device__ __forceinline__ void produce(const void* src, uint32_t dst, uint32_t full, uint32_t empty, Ring& r) {
#pragma unroll 1
  for (int kt = 0; kt < KT; kt++) {
    if constexpr (LIM > 0) mbar_wait(full + (r.s >= LIM ? r.s - LIM : r.s + N - LIM) * 8, r.s >= LIM ? r.ph : r.ph ^ 1);
    mbar_wait(empty + r.s * 8, r.ph ^ 1);
    mbar_expect_tx(full + r.s * 8, BYTES);
    bulk_g2s(dst + r.s * STRIDE, (const uint8_t*)src + kt * BYTES, BYTES, full + r.s * 8);
    ring_adv<N>(r);
  }
}
__device__ __forceinline__ void bulk_s2g(void* dst, uint32_t src, uint32_t bytes) {
  asm volatile("cp.async.bulk.global.shared::cta.bulk_group [%0], [%1], %2;\ncp.async.bulk.commit_group;" ::"l"(dst), "r"(src), "r"(bytes) : "memory");
}
template <int BK, bool B128> __device__ __forceinline__ uint64_t b_desc(uint32_t addr) { return B128 ? mk_desc(addr, 8192, 1024, 1) : mk_desc(addr, BK * 32, 256, 3); }

template <int BN, int MT, int KT, int BK, int APT, bool TILED, bool B128, bool HR = false>
__device__ __forceinline__ void mainloop(float (&acc)[MT][BN / 2], uint32_t sbase, uint32_t bars, int lane, int wg, int a0, bool pass, Ring& rb, int cont = 0, int dbgk = -1) {
  constexpr int NA = HR ? 5 : SA, AST = HR ? 12288 : STAGE, FA = HR ? BAR_FH : BAR_FA, EA = HR ? BAR_EH : BAR_EA;
  Ring ra{(uint32_t)a0 % NA, ((uint32_t)a0 / NA) & 1};
  if (HR || a0 != 0) named_bar(6 - wg, 256);
  DBG(long long cs0 = clock64();)
  mbar_wait(bars + BAR_FB + rb.s * 8, rb.ph);
  mbar_wait(bars + FA + ra.s * 8, ra.ph);
  DBG(long long wf = clock64() - cs0;)
  const uint64_t da0 = TILED ? mk_desc(sbase, 128, BK * 16, 0) : mk_desc(sbase, 16, 1024, 1), db0 = b_desc<BK, B128>(sbase + SM_B);
  uint32_t relA = 0, relB = 0;
#pragma unroll 1
  for (int kt = 0; kt < KT; kt += APT) {
#pragma unroll
    for (int u = 0; u < APT; u++) {
      const bool more = u + 1 < APT || kt + APT < KT;
      if (!more && pass) asm volatile("bar.arrive %0, 256;" ::"r"(5 + wg) : "memory");
      const uint64_t da = da0 + ra.s * (AST / 16) + u * 512, db = db0 + rb.s * (STAGE / 16);
      wg_fence();
#pragma unroll
      for (int k = 0; k < BK / 16; k++)
#pragma unroll
        for (int m = 0; m < MT; m++) wgmma_ss(acc[m], da + m * 512 + k * (TILED ? 16 : 2), db + k * (B128 ? 128 : 32), (kt | u | k | cont) != 0);
      wg_commit();
      const uint32_t curA = u == APT - 1 ? bars + EA + ra.s * 8 : 0, curB = bars + BAR_EB + rb.s * 8;
      if (u == APT - 1) ring_adv<NA>(ra);
      ring_adv<SB>(rb);
      bool ok = mbar_test(bars + BAR_FB + rb.s * 8, rb.ph);
      if (u == APT - 1) ok &= mbar_test(bars + FA + ra.s * 8, ra.ph);
      wg_wait<1>();
      if (lane == 0 && relB) { if (relA) mbar_arrive(relA); mbar_arrive(relB); }
      relA = curA; relB = curB;
      if (!ok && more) { mbar_wait(bars + BAR_FB + rb.s * 8, rb.ph); mbar_wait(bars + FA + ra.s * 8, ra.ph); }
    }
  }
  wg_wait<0>();
  DBG(if (dbgk >= 0 && (threadIdx.x & 127) == 0) { long long* d = g_dbg + (blockIdx.x * 16 + dbgk * 2 + wg) * 4; d[0] = clock64() - cs0; d[1] = wf; d[2] = 0; d[3] = 0; })
#pragma unroll
  for (int m = 0; m < MT; m++) fence_regs(acc[m]);
  if (lane == 0) { mbar_arrive(relA); mbar_arrive(relB); }
}
__device__ __forceinline__ void acquire_stage(uint32_t bars, const Ring& rb, uint32_t s) { mbar_wait(bars + BAR_EB + s * 8, s >= rb.s ? rb.ph ^ 1 : rb.ph); }

template <bool BIAS, bool FINAL>
__device__ __forceinline__ void epi_resid(const float (&acc)[40], uint32_t (&res)[20], const uint32_t (&bias)[10], bf16* out, float2* st,
                                          uint8_t* stage, int row0, int j, int lane) {
  const int q = lane & 3;
  uint32_t* o0 = FINAL ? (uint32_t*)(stage + (row0 & 63) * 160) + q : (uint32_t*)out + lane;
  float s0 = 0.f, t0 = 0.f, s1 = 0.f, t1 = 0.f;
#pragma unroll
  for (int b = 0; b < 10; b++) {
    const float bl = BIAS ? bf_lo(bias[b]) : 0.f, bh = BIAS ? bf_hi(bias[b]) : 0.f;
    const uint32_t p0 = pack_bf16(acc[4 * b] + bl + bf_lo(res[2 * b]), acc[4 * b + 1] + bh + bf_hi(res[2 * b]));
    const uint32_t p1 = pack_bf16(acc[4 * b + 2] + bl + bf_lo(res[2 * b + 1]), acc[4 * b + 3] + bh + bf_hi(res[2 * b + 1]));
    res[2 * b] = p0; res[2 * b + 1] = p1;
    if (FINAL) { o0[b * 4] = p0; o0[b * 4 + 320] = p1; }
    else {
      const int ln = x_line(row0, j * 10 + b);
      o0[ln * 32] = p0; o0[ln * 32 + 256] = p1;
      const float a = bf_lo(p0), c = bf_hi(p0), d = bf_lo(p1), e = bf_hi(p1);
      s0 += a + c; t0 = fmaf(a, a, fmaf(c, c, t0));
      s1 += d + e; t1 = fmaf(d, d, fmaf(e, e, t1));
    }
  }
  if (!FINAL) {
#pragma unroll
    for (int m = 1; m < 4; m <<= 1) {
      s0 += __shfl_xor_sync(0xffffffffu, s0, m); t0 += __shfl_xor_sync(0xffffffffu, t0, m);
      s1 += __shfl_xor_sync(0xffffffffu, s1, m); t1 += __shfl_xor_sync(0xffffffffu, t1, m);
    }
    if (q < 2) st[j * SEQ + row0 + q * 8] = q ? make_float2(s1, t1) : make_float2(s0, t0);
  }
}
__device__ __forceinline__ void publish(unsigned int* f, int wg, int tid) {
  named_bar(2 + wg, 128);
  if ((tid & 127) == 0) flag_signal(f);
}
__device__ __forceinline__ float gelu_half(float s) {
  const float z = s * fmaf(s * s, 8.f * 0.044715f * 0.7978845608028654f, 2.f * 0.7978845608028654f);
  float th;
  asm("tanh.approx.f32 %0, %1;" : "=f"(th) : "f"(z));
  return fmaf(s, th, s);
}
template <bool DOUBLE> __device__ __forceinline__ float2 row_coef(float s, float t) {
  const float mean = s * (1.f / DM);
  const float var = fmaxf(fmaf(-mean, mean, t * (1.f / DM)), 0.f);
  float r = rsqrtf(var + LN_EPS);
  if (DOUBLE) r *= 0.5f * rsqrtf(var * r * r + LN_EPS);
  return make_float2(r, -r * mean);
}
template <bool DOUBLE, int NP> __device__ __forceinline__ void reduce_stats(const float2* st, float2* dst, int i, int lane) {
  float4 v[2][NP];
#pragma unroll
  for (int rr = 0; rr < 2; rr++)
#pragma unroll
    for (int k = 0; k < NP; k++) v[rr][k] = __ldcg((const float4*)(st + k * SEQ + i * 128 + rr * 64) + lane);
#pragma unroll
  for (int rr = 0; rr < 2; rr++) {
    float s0 = 0.f, t0 = 0.f, s1 = 0.f, t1 = 0.f;
#pragma unroll
    for (int k = 0; k < NP; k++) { s0 += v[rr][k].x; t0 += v[rr][k].y; s1 += v[rr][k].z; t1 += v[rr][k].w; }
    dst[rr * 64 + lane * 2] = row_coef<DOUBLE>(s0, t0);
    dst[rr * 64 + lane * 2 + 1] = row_coef<DOUBLE>(s1, t1);
  }
}

template <int PH, bool FIRST, bool LAST>
__global__ void __launch_bounds__(CHAIN_THREADS, 1) chain_kernel(const __grid_constant__ ChainParams p) {
  extern __shared__ __align__(1024) uint8_t smem[];
  const uint32_t sbase = smem_u32(smem), bars = sbase + SM_BAR;
  float* cs = (float*)(smem + SM_CS);
  uint32_t* sb1 = (uint32_t*)(smem + SM_B1);
  const int tid = threadIdx.x, lane = tid & 31, warp = __shfl_sync(0xffffffffu, tid >> 5, 0);
  if (tid == 32) {
    unsigned int* claim = p.flags + 64;
    uint32_t smid;
    asm volatile("mov.u32 %0, %%smid;" : "=r"(smid));
    int t = smid < 160 ? p.pref[smid] : -1;
    if (t >= 0 && atomicExch(claim + t, 1u) != 0u) t = -2;
    if (t == -1) {
#pragma unroll 1
      for (int it = 0; it < 100000; it++) {
        if (*(volatile unsigned int*)(claim + 128) >= 128u) break;
        __nanosleep(200);
      }
    }
    if (t < 0) {
      t = -1;
      if (*(volatile unsigned int*)(claim + 128) < 128u) {
#pragma unroll 1
        for (int c = 0; c < 128 && t < 0; c++)
          if (atomicExch(claim + c, 1u) == 0u) t = c;
      }
    }
    if (t >= 0) atomicAdd(claim + 128, 1u);
    *(volatile int*)(smem + SM_BAR + BAR_TILE) = t;
  }
  unsigned int* fl = p.flags;
  if (tid == 0) {
    for (int s = 0; s < SA; s++) { mbar_init(bars + BAR_FA + s * 8, 1); mbar_init(bars + BAR_EA + s * 8, 4); }
    for (int s = 0; s < SB; s++) { mbar_init(bars + BAR_FB + s * 8, 1); mbar_init(bars + BAR_EB + s * 8, 8); }
    mbar_init(bars + BAR_AUX, 32); mbar_init(bars + BAR_AUX + 8, 32);
    mbar_init(bars + BAR_AUX + 16, FIRST ? 37 : 32); mbar_init(bars + BAR_AUX + 24, 32);
    for (int s = 0; s < 5; s++) { mbar_init(bars + BAR_FH + s * 8, 1); mbar_init(bars + BAR_EH + s * 8, 4); }
    asm volatile("fence.mbarrier_init.release.cluster;" ::: "memory");
  }
  if (tid == 256) {
    if (FIRST) {
      prefetch_map(&p.a_x); prefetch_map(&p.b_wqkv); prefetch_map(&p.b_w1); prefetch_map(&p.b_wo); prefetch_map(&p.b_w2);
    }
    if (LAST) prefetch_map(&p.o_out);
  }
  __syncthreads();
  pdl_launch();
  const int tile = *(volatile int*)(smem + SM_BAR + BAR_TILE);
  if (tile < 0) return;
  const int g = tile >> 4, c = tile & 15;
  if (tid == 0) TS(p.kid, 0);

  if (warp == 9) {
    if (lane == 0) {
      if (FIRST) {
#pragma unroll 1
        for (int kt = 0; kt < 10; kt++) {
          if (kt >= KLIM) mbar_wait(bars + BAR_FB + (kt - KLIM) * 8, 0);
          mbar_expect_tx(bars + BAR_FB + kt * 8, STAGE);
          tma_3d(sbase + SM_B + kt * STAGE, &p.b_wqkv, 0, c, kt * 64, bars + BAR_FB + kt * 8);
          tma_3d(sbase + SM_B + kt * STAGE + 8192, &p.b_wqkv, 64, c, kt * 64, bars + BAR_FB + kt * 8);
        }
#pragma unroll 1
        for (int kt = g; kt < 10; kt += 8) {
          mbar_wait(bars + BAR_FB + kt * 8, 0);
          bulk_s2g(g_wt + WT_QKV + (c * 10 + kt) * STAGE, sbase + SM_B + kt * STAGE, STAGE);
        }
        asm volatile("cp.async.bulk.wait_group.read 0;" ::: "memory");
        mbar_arrive(bars + BAR_AUX + 16);
        asm volatile("cp.async.bulk.wait_group 0;" ::: "memory");
      } else {
        Ring r{0, 0};
        produce<10, 10240, SB>(g_wt + WT_WO + (c >> 1) * 10 * 10240, sbase + SM_B, bars + BAR_FB, bars + BAR_EB, r);
        produce<10, 14336, SB, STAGE, BL1>(g_wt + WT_W1 + c * 10 * 14336, sbase + SM_B, bars + BAR_FB, bars + BAR_EB, r);
        produce<18, 15360, SB, STAGE, BL2>(g_wt + WT_W2 + (c >> 1) * 18 * 15360, sbase + SM_B, bars + BAR_FB, bars + BAR_EB, r);
        if (PH & PH_QKV) produce<10, STAGE, SB, STAGE, BL3>(g_wt + WT_QKV + c * 10 * STAGE, sbase + SM_B, bars + BAR_FB, bars + BAR_EB, r);
      }
    }
  } else if (warp == 8) {
    if (lane == 0) {
      Ring r{0, 0};
      if (FIRST) {
#pragma unroll 1
        for (int t = 0; t < 20; t++) {
          mbar_wait(bars + BAR_EA + r.s * 8, r.ph ^ 1);
          mbar_expect_tx(bars + BAR_FA + r.s * 8, STAGE);
          tma_2d(sbase + r.s * STAGE, &p.a_x, (t % 10) * 64, g * 256 + (t / 10) * 128, bars + BAR_FA + r.s * 8);
          ring_adv<SA>(r);
        }
#pragma unroll 1
        for (int n = 0; n < 3; n++) {
          const int job = n * 128 + tile;
          const uint32_t st = sbase + SM_B + (3 + n) * STAGE, bar = bars + BAR_JOB + n * 8;
          mbar_wait(bars + BAR_EB + (3 + n) * 8, 0);
          const CUtensorMap* m = job < 160 ? &p.b_w1 : (job < 240 ? &p.b_wo : &p.b_w2);
          const int t = job < 160 ? job : (job < 240 ? job - 160 : job - 240);
          const int nkt = job < 240 ? 10 : 18, bk = job < 240 ? 64 : 96, nbox = job < 160 ? 7 : 5;
          const int blk = job < 160 ? (t / 10) >> 1 : t / nkt, c0 = job < 160 ? ((t / 10) & 1) * 112 : 0;
          mbar_expect_tx(bar, nbox * bk * 32);
#pragma unroll 1
          for (int b = 0; b < nbox; b++) tma_3d(st + b * bk * 32, m, c0 + b * 16, blk, (t % nkt) * bk, bar);
        }
#pragma unroll 1
        for (int n = 0; n < 3; n++) {
          const int job = n * 128 + tile;
          mbar_wait(bars + BAR_JOB + n * 8, 0);
          const int off = job < 160 ? WT_W1 + job * 14336 : (job < 240 ? WT_WO + (job - 160) * 10240 : WT_W2 + (job - 240) * 15360);
          bulk_s2g(g_wt + off, sbase + SM_B + (3 + n) * STAGE, job < 160 ? 14336 : (job < 240 ? 10240 : 15360));
        }
        asm volatile("cp.async.bulk.wait_group 0;" ::: "memory");
      } else {
        pdl_wait();
        TS(p.kid, 16);
#pragma unroll 1
        for (int s = 0; s < 2; s++) produce<5, 16384, SA>((const uint8_t*)g_o + (g * 4 + s * 2 + (c & 1)) * 10 * 8192, sbase, bars + BAR_FA, bars + BAR_EA, r);
#pragma unroll 1
        for (int s = 0; s < 2; s++) {
          flag_wait(fl + g * 2 + s, 16); fence_async_global(); TS(p.kid, 17 + s * 3);
          produce<10, 16384, SA>((const uint8_t*)g_x1 + (g * 2 + s) * 10 * 16384, sbase, bars + BAR_FA, bars + BAR_EA, r);
        }
        Ring rh{0, 0};
#pragma unroll 1
        for (int s = 0; s < SA; s++) mbar_wait(bars + BAR_EA + s * 8, s >= r.s ? r.ph ^ 1 : r.ph);
        const uint8_t* hsrc = (const uint8_t*)g_h + (g * 4 + (c & 1)) * 18 * 12288;
#pragma unroll 1
        for (int s = 0; s < 2; s++) {
          flag_wait(fl + 16 + g * 2 + s, 16); fence_async_global(); TS(p.kid, 18 + s * 3);
          produce<10, 12288, 5, 12288>(hsrc + s * 36 * 12288, sbase, bars + BAR_FH, bars + BAR_EH, rh);
        }
#pragma unroll 1
        for (int s = 0; s < 2; s++) produce<8, 12288, 5, 12288>(hsrc + (s * 36 + 10) * 12288, sbase, bars + BAR_FH, bars + BAR_EH, rh);
        if (PH & PH_QKV) {
#pragma unroll 1
          for (int s = 0; s < 5; s++) mbar_wait(bars + BAR_EH + s * 8, s >= rh.s ? rh.ph ^ 1 : rh.ph);
        }
        if (PH & PH_QKV) {
#pragma unroll 1
          for (int s = 0; s < 2; s++) {
            flag_wait(fl + 32 + g * 2 + s, 16); fence_async_global(); TS(p.kid, 19 + s * 3);
            produce<10, 16384, SA>((const uint8_t*)g_x2 + (g * 2 + s) * 10 * 16384, sbase, bars + BAR_FA, bars + BAR_EA, r);
          }
        }
      }
    }
  } else if (warp == 10) {
    float2* srow = (float2*)(smem + SM_ROW);
    if (FIRST) {
      named_bar(4, 160);
      if (lane == 0) flag_signal(fl + g * 2 + (c >> 3));
#pragma unroll 1
      for (int s = 0; s < 2; s++) {
        if (lane == 0) flag_wait(fl + g * 2 + s, 8);
        __syncwarp();
        reduce_stats<false, 2>(g_s.st0, srow + s * 128, g * 2 + s, lane);
        mbar_arrive(bars + BAR_AUX + 16 + s * 8);
      }
#pragma unroll 1
      for (int n = 0; n < 2; n++) {
        const int job = n * 128 + tile;
        if (job < 160) {
          mbar_wait(bars + BAR_JOB + n * 8, 0);
          const uint8_t* base = smem + SM_B + (3 + n) * STAGE + ((lane & 15) >> 1) * 2048 + (lane >> 4) * 1024;
          float a[8];
#pragma unroll
          for (int e = 0; e < 8; e++) a[e] = 0.f;
#pragma unroll 4
          for (int r = 0; r < 32; r++) {
            const uint4 v = *(const uint4*)(base + r * 32 + (((lane & 1) ^ ((r >> 2) & 1)) * 16));
            a[0] += bf_lo(v.x); a[1] += bf_hi(v.x); a[2] += bf_lo(v.y); a[3] += bf_hi(v.y);
            a[4] += bf_lo(v.z); a[5] += bf_hi(v.z); a[6] += bf_lo(v.w); a[7] += bf_hi(v.w);
          }
#pragma unroll
          for (int e = 0; e < 8; e++) a[e] += __shfl_xor_sync(0xffffffffu, a[e], 16);
          if (lane < 14) {
            float4* d = (float4*)(g_s.csp_w1 + (job % 10) * 1792 + (job / 10) * 112 + lane * 8);
            d[0] = make_float4(a[0], a[1], a[2], a[3]); d[1] = make_float4(a[4], a[5], a[6], a[7]);
          }
        }
      }
    } else {
      if (lane < 28) {
        float4 v[10], a = make_float4(0.f, 0.f, 0.f, 0.f);
#pragma unroll
        for (int k = 0; k < 10; k++) v[k] = __ldcg((const float4*)(g_s.csp_w1 + k * 1792 + c * 112) + lane);
#pragma unroll
        for (int k = 0; k < 10; k++) { a.x += v[k].x; a.y += v[k].y; a.z += v[k].z; a.w += v[k].w; }
        ((float4*)cs)[lane] = a;
      }
      for (int k = lane; k < 56; k += 32) {
        const int col = (c >> 1) * 216 + (c & 1) * 112 + k * 2;
        const uint32_t v = col < FF ? __ldg((const uint32_t*)(p.b1 + col)) : 0u;
        sb1[k] = pack_bf16(0.5f * bf_lo(v), 0.5f * bf_hi(v));
      }
      pdl_wait();
#pragma unroll 1
      for (int s = 0; s < 2; s++) {
        if (lane == 0) flag_wait(fl + g * 2 + s, 16);
        __syncwarp();
        reduce_stats<true, 8>(g_s.st1, srow + s * 128, g * 2 + s, lane);
        mbar_arrive(bars + BAR_AUX + s * 8);
      }
      if (PH & PH_QKV) {
        const float4 cq = lane < 30 ? __ldcg((const float4*)(g_s.cs_qkv + c * 120) + lane) : make_float4(0.f, 0.f, 0.f, 0.f);
#pragma unroll 1
        for (int s = 0; s < 2; s++) {
          if (lane == 0) { if (s == 0) flag_wait(fl + 16 + g * 2 + 1, 16); flag_wait(fl + 32 + g * 2 + s, 16); }
          __syncwarp();
          if (s == 0 && lane < 30) ((float4*)cs)[lane] = cq;
          reduce_stats<false, 8>(g_s.st2, srow + s * 128, g * 2 + s, lane);
          mbar_arrive(bars + BAR_AUX + 16 + s * 8);
        }
      }
    }
  } else {
    const int wg = warp >> 2, w4 = warp & 3, q = lane & 3;
    const int rbk = g * 2 + wg, rl = w4 * 16 + (lane >> 2);
    const int rowS = rbk * 128 + (c & 1) * 64 + rl, jS = c >> 1;
    const float2* srow = (const float2*)(smem + SM_ROW) + wg * 128;
    const bool t0 = (tid & 127) == 0;
    Ring rb{0, 0};
    uint32_t res[20], bias2[10];
    if (FIRST) {
      if (wg == 1) {
        const int xrow = g * 256 + c * 16 + (w4 & 1) * 8 + (lane >> 2), xcg = (w4 >> 1) * 40 + q;
        uint4 xv[10];
#pragma unroll
        for (int k = 0; k < 10; k++) xv[k] = __ldg((const uint4*)(p.xin + (size_t)xrow * DM) + xcg + k * 4);
        float xs = 0.f, xt = 0.f;
#pragma unroll
        for (int k = 0; k < 10; k++) {
          const uint32_t e[4] = {xv[k].x, xv[k].y, xv[k].z, xv[k].w};
#pragma unroll
          for (int m = 0; m < 4; m++) { const float a = bf_lo(e[m]), b = bf_hi(e[m]); xs += a + b; xt = fmaf(a, a, fmaf(b, b, xt)); }
        }
#pragma unroll
        for (int m = 1; m < 4; m <<= 1) { xs += __shfl_xor_sync(0xffffffffu, xs, m); xt += __shfl_xor_sync(0xffffffffu, xt, m); }
        if (q == 0) g_s.st0[(w4 >> 1) * SEQ + xrow] = make_float2(xs, xt);
        asm volatile("bar.arrive 4, 160;" ::: "memory");
#pragma unroll
        for (int k = 0; k < 10; k++) *((uint4*)g_x0 + x_line(xrow, xcg + k * 4) * 8 + (xrow & 7)) = xv[k];
        float o[60];
        const uint32_t one = 0x3F803F80u;
#pragma unroll 1
        for (int kt = 0; kt < 10; kt++) {
          mbar_wait(bars + BAR_FB + kt * 8, 0);
          wg_fence();
#pragma unroll
          for (int k = 0; k < 4; k++) wgmma_rs_n120<1>(o, one, one, one, one, b_desc<64, true>(sbase + SM_B + kt * STAGE) + k * 128, (kt | k) != 0);
          wg_commit();
        }
        wg_wait<0>();
        fence_regs(o);
        if ((tid & 127) < 4) {
#pragma unroll
          for (int b = 0; b < 15; b++) {
            *(float2*)(cs + b * 8 + q * 2) = make_float2(o[4 * b], o[4 * b + 1]);
            if (g == 0) *(float2*)(g_s.cs_qkv + c * 120 + b * 8 + q * 2) = make_float2(o[4 * b], o[4 * b + 1]);
          }
          mbar_arrive(bars + BAR_AUX + 16);
        }
        named_bar(3, 128);
      }
    } else {
#pragma unroll
      for (int b = 0; b < 10; b++) {
        const uint32_t* r0 = (const uint32_t*)p.xres + x_line(rowS, jS * 10 + b) * 32 + lane;
        res[2 * b] = __ldcg(r0); res[2 * b + 1] = __ldcg(r0 + 256);
      }
      {
        float acc[1][40];
        if (t0) TS(p.kid, 1 + wg * 24);
        mainloop<80, 1, 10, 64, 2, true, false>(acc, sbase, bars, lane, wg, wg * 5, wg != 0, rb, 0, p.kid == 2 ? 0 : -1);
        if (t0) TS(p.kid, 2 + wg * 24);
        pdl_wait();
        epi_resid<false, false>(acc[0], res, bias2, g_x1, g_s.st1, smem, rowS, jS, lane);
        if (wg == 0) asm volatile("bar.arrive 5, 256;" ::: "memory");
        publish(fl + rbk, wg, tid);
      }
      {
        float acc[2][56];
        if (t0) TS(p.kid, 3 + wg * 24);
        mainloop<112, 2, 10, 64, 1, true, false>(acc, sbase, bars, lane, wg, 10 + wg * 10, true, rb, 0, p.kid == 2 ? 1 : -1);
        if (t0) TS(p.kid, 4 + wg * 24);
        mbar_wait(bars + BAR_AUX + wg * 8, 0);
        const float2 c0 = srow[rl], c1 = srow[rl + 8], c2 = srow[rl + 64], c3 = srow[rl + 72];
        const int cg0 = (c >> 1) * 27 + (c & 1) * 14;
        uint32_t* o0 = (uint32_t*)g_h + h_line(rbk * 128 + rl, cg0) * 32 + lane;
        int kg = cg0 % 12;
#pragma unroll
        for (int b = 0; b < 14; b++) {
          if (b < 13 || !(c & 1)) {
            const float2 cc = *(const float2*)(cs + b * 8 + q * 2);
            const uint32_t bb = sb1[b * 4 + q];
            const float bl = bf_lo(bb), bh = bf_hi(bb);
            o0[0] = pack_bf16(gelu_half(fmaf(c0.x, acc[0][4 * b], fmaf(c0.y, cc.x, bl))), gelu_half(fmaf(c0.x, acc[0][4 * b + 1], fmaf(c0.y, cc.y, bh))));
            o0[384] = pack_bf16(gelu_half(fmaf(c1.x, acc[0][4 * b + 2], fmaf(c1.y, cc.x, bl))), gelu_half(fmaf(c1.x, acc[0][4 * b + 3], fmaf(c1.y, cc.y, bh))));
            o0[18 * 3072] = pack_bf16(gelu_half(fmaf(c2.x, acc[1][4 * b], fmaf(c2.y, cc.x, bl))), gelu_half(fmaf(c2.x, acc[1][4 * b + 1], fmaf(c2.y, cc.y, bh))));
            o0[18 * 3072 + 384] = pack_bf16(gelu_half(fmaf(c3.x, acc[1][4 * b + 2], fmaf(c3.y, cc.x, bl))), gelu_half(fmaf(c3.x, acc[1][4 * b + 3], fmaf(c3.y, cc.y, bh))));
            o0 += (++kg == 12) ? (96 - 11) * 32 : 32;
            if (kg == 12) kg = 0;
          }
        }
        if (t0) TS(p.kid, 5 + wg * 24);
        publish(fl + 16 + rbk, wg, tid);
      }
      {
#pragma unroll
        for (int b = 0; b < 10; b++) bias2[b] = __ldg((const uint32_t*)(p.b2 + jS * 80) + b * 4 + q);
        float acc[1][40];
        mainloop<80, 1, 10, 96, 1, true, false, true>(acc, sbase, bars, lane, wg, wg * 10, true, rb, 0, p.kid == 2 ? 2 : -1);
        mainloop<80, 1, 8, 96, 1, true, false, true>(acc, sbase, bars, lane, wg, 20 + wg * 8, LAST ? wg == 0 : wg != 0, rb, 1, p.kid == 2 ? 3 : -1);
        if (t0) TS(p.kid, 6 + wg * 24);
        if (LAST) {
          const uint32_t st = (rb.s + wg) % SB;
          acquire_stage(bars, rb, st);
          epi_resid<true, true>(acc[0], res, bias2, nullptr, nullptr, smem + SM_B + st * STAGE, rowS, jS, lane);
          asm volatile("fence.proxy.async.shared::cta;" ::: "memory");
          named_bar(2 + wg, 128);
          if (t0) {
            asm volatile("cp.async.bulk.tensor.2d.global.shared::cta.bulk_group [%0, {%2, %3}], [%1];" ::"l"(&p.o_out), "r"(sbase + SM_B + st * STAGE), "r"(jS * 80),
                         "r"(rbk * 128 + (c & 1) * 64) : "memory");
            asm volatile("cp.async.bulk.commit_group;\ncp.async.bulk.wait_group 0;" ::: "memory");
          }
        } else {
          epi_resid<true, false>(acc[0], res, bias2, g_x2, g_s.st2, smem, rowS, jS, lane);
          if (wg == 0) asm volatile("bar.arrive 5, 256;" ::: "memory");
          publish(fl + 32 + rbk, wg, tid);
        }
      }
    }
    if (PH & PH_QKV) {
      float acc[2][60];
      if (t0) TS(p.kid, 10 + wg * 2);
      mainloop<120, 2, 10, 64, 1, !FIRST, true>(acc, sbase, bars, lane, wg, (FIRST ? 0 : 30) + wg * 10, wg == 0, rb, 0, p.kid == 2 ? 4 : 5);
      if (t0) TS(p.kid, 11 + wg * 2);
      mbar_wait(bars + BAR_AUX + 16 + wg * 8, 0);
      const float QS = 0.22360679774997896f * 1.4426950408889634f;
      unsigned int* smax = sb1 + 16 + wg * 8;
      if ((tid & 127) < 6) smax[tid & 127] = 0u;
      named_bar(2 + wg, 128);
      int off[5];
#pragma unroll
      for (int m = 0; m < 5; m++) {
        const int cc = m * 8 + q * 2, hh = cc >= 20, d = cc - hh * 20;
        off[m] = hh * 6144 + (d >> 3) * 128 + (d & 7) * 2;
      }
#pragma unroll
      for (int pr = 0; pr < 3; pr++) {
        const int part = (c * 6 + pr * 2) >> 5;
        float nrm[2];
        const uint32_t sst = (rb.s + pr) % SB, soff = wg ? pr * STAGE : SM_B + sst * STAGE;
        if (wg == 0) acquire_stage(bars, rb, sst);
        uint8_t* stg = smem + soff + w4 * 768 + (lane >> 2) * 16;
#pragma unroll
        for (int mt = 0; mt < 2; mt++) {
          const float2 c0 = srow[mt * 64 + rl], c1 = srow[mt * 64 + rl + 8];
          const bool mu0 = is_mufu(mt * 8 + w4 * 2), mu1 = is_mufu(mt * 8 + w4 * 2 + 1), mu = (q & 1) ? mu1 : mu0;
          const float s0 = part == 0 ? QS : (part == 1 && !mu0 ? 0x1p-22f : 1.f), s1 = part == 0 ? QS : (part == 1 && !mu1 ? 0x1p-22f : 1.f);
          const float a0 = c0.x * s0, b0 = c0.y * s0, a1 = c1.x * s1, b1 = c1.y * s1;
          float nA0 = 0.f, nA1 = 0.f, nB0 = 0.f, nB1 = 0.f;
#pragma unroll
          for (int m = 0; m < 5; m++) {
            const int b = pr * 5 + m;
            const float2 cc = *(const float2*)(cs + b * 8 + q * 2);
            uint8_t* ptr = stg + off[m] + mt * 3072;
            const float v0 = fmaf(a0, acc[mt][4 * b], b0 * cc.x), v1 = fmaf(a0, acc[mt][4 * b + 1], b0 * cc.y);
            const float v2 = fmaf(a1, acc[mt][4 * b + 2], b1 * cc.x), v3 = fmaf(a1, acc[mt][4 * b + 3], b1 * cc.y);
            *(uint32_t*)ptr = pack_bf16(v0, v1);
            *(uint32_t*)(ptr + 384) = pack_bf16(v2, v3);
            const float n0 = fmaf(v0, v0, v1 * v1), n1 = fmaf(v2, v2, v3 * v3);
            if (m < 2) { nA0 += n0; nA1 += n1; } else if (m > 2) { nB0 += n0; nB1 += n1; }
            else if (q < 2) { nA0 += n0; nA1 += n1; } else { nB0 += n0; nB1 += n1; }
          }
          const uint2 ex = part == 0 ? make_uint2(0x3F803F80u, 0x00003F80u)
                                     : (part == 1 ? (mu ? make_uint2(0u, 0u) : make_uint2(0x377C3C00u, 0x00003020u)) : make_uint2(0x00003F80u, 0u));
          *(uint2*)(stg + mt * 3072 + (q >> 1) * 6144 + (q & 1) * 384 + 264) = ex;
          float x = (q & 1) ? nA1 : nA0, y = (q & 1) ? nB1 : nB0;
          x += __shfl_xor_sync(0xffffffffu, (q & 1) ? nA0 : nA1, 1);
          y += __shfl_xor_sync(0xffffffffu, (q & 1) ? nB0 : nB1, 1);
          float n = (q & 2) ? y : x;
          n += __shfl_xor_sync(0xffffffffu, (q & 2) ? x : y, 2);
          nrm[mt] = (part == 1 && !mu) ? n * 0x1p44f : n;
        }
        asm volatile("fence.proxy.async.shared::cta;" ::: "memory");
        named_bar(2 + wg, 128);
        if ((tid & 127) < 2) bulk_s2g((uint8_t*)g_qkv + (size_t)(c * 6 + pr * 2 + lane) * HEAD_BYTES + rbk * 6144, sbase + soff + lane * 6144, 6144);
        if (part < 2) atomicMax(smax + pr * 2 + (q >> 1), max(__float_as_uint(nrm[0]) & 0x7FFFFFFFu, __float_as_uint(nrm[1]) & 0x7FFFFFFFu));
      }
      named_bar(2 + wg, 128);
      if ((tid & 127) < 6 && c * 6 + (tid & 127) < 64) atomicMax(fl + NORM_OFF + c * 6 + (tid & 127), smax[tid & 127]);
      if ((tid & 127) < 2) asm volatile("cp.async.bulk.wait_group 0;" ::: "memory");
    }
    if (t0) TS(p.kid, 14 + wg);
  }
}

__device__ __forceinline__ uint32_t exp2_poly_pair(float a0, float a1) {
  const uint32_t v = __byte_perm(__float_as_uint(a0), __float_as_uint(a1), 0x7430);
  const uint32_t e = __byte_perm(__float_as_uint(a0), __float_as_uint(a1), 0x6521);
  uint32_t u;
  asm("fma.rn.f16x2 %0, %1, %2, %3;" : "=r"(u) : "r"(v), "r"(0x1d611d61u), "r"(0xa012a012u));
  asm("fma.rn.f16x2 %0, %1, %2, %3;" : "=r"(u) : "r"(u), "r"(v), "r"(0x21622162u));
  return e * 128u + u;
}
constexpr int ATT_SMEM = 2 * HEAD_BYTES + 256;

__device__ __forceinline__ void att_store(const float (&O)[12], int row0, int h, int lane) {
  const float l0 = __shfl_sync(0xffffffffu, O[8], (lane & ~3) | 2), l1 = __shfl_sync(0xffffffffu, O[10], (lane & ~3) | 2);
  const float r0 = __fdividef(1.f, l0), r1 = __fdividef(1.f, l1);
#pragma unroll
  for (int c = 0; c < 3; c++)
    if (c < 2 || (lane & 3) < 2) {
      const int col = h * 20 + c * 8 + (lane & 3) * 2;
      uint32_t* o0 = (uint32_t*)g_o + o_line(row0, col >> 3) * 32 + (row0 & 7) * 4 + ((col & 7) >> 1);
      o0[0] = pack_bf16(O[4 * c] * r0, O[4 * c + 1] * r0);
      o0[256] = pack_bf16(O[4 * c + 2] * r1, O[4 * c + 3] * r1);
    }
}

__global__ void __launch_bounds__(512, 1) att_kernel(const unsigned int* norms, unsigned int* reset_a, unsigned int* reset_b, unsigned int* reset_c, const uint32_t* zeros, int kid) {
  extern __shared__ __align__(1024) uint8_t smem[];
  const uint32_t sK = smem_u32(smem), sV = sK + HEAD_BYTES, bars = sV + HEAD_BYTES + 128;
  const int h = blockIdx.x >> 2, qt = blockIdx.x & 3;
  const int tid = threadIdx.x, lane = tid & 31, wg = __shfl_sync(0xffffffffu, tid >> 7, 0), warp = (tid >> 5) & 3;
  if (tid == 0) {
    for (int c = 0; c < 8; c++) mbar_init(bars + c * 8, 1);
    asm volatile("fence.mbarrier_init.release.cluster;" ::: "memory");
  }
  const uint32_t z0 = __ldg(zeros + (tid & 1)), z1 = __ldg(zeros + 2 + (tid & 1));
  __syncthreads();
  if (tid == 0) TS(kid, 0);
  pdl_wait();
  pdl_launch();
  if (tid == 0) TS(kid, 1);
  const uint8_t* gq = (const uint8_t*)g_qkv + (size_t)h * HEAD_BYTES;
  if (blockIdx.x == 0 && tid < NORM_OFF) { reset_a[tid] = 0u; if (tid < 64) reset_b[tid] = 0u; if (reset_c) reset_c[tid] = 0u; }
  const uint64_t dK = mk_desc(sK, 128, 384, 0);
  const uint64_t dV = mk_desc(sV, 384, 128, 0);
  bool bad = !(__uint_as_float(__ldcg(norms + h)) * __uint_as_float(__ldcg(norms + 32 + h)) <= 3500.f);
  uint32_t q[6];
  auto load_q = [&](int tt) {
    const int row0 = qt * 512 + (tt * 4 + wg) * 64 + warp * 16 + (lane >> 2);
    const uint32_t* qa = (const uint32_t*)(gq + (row0 >> 3) * 384 + (row0 & 7) * 16) + (lane & 3);
    q[0] = __ldcg(qa); q[1] = __ldcg(qa + 96); q[2] = __ldcg(qa + 32); q[3] = __ldcg(qa + 128); q[4] = __ldcg(qa + 64); q[5] = __ldcg(qa + 160);
  };
  load_q(0);
  auto load_kv = [&](int c) {
    const int k0 = c == 0 ? 0 : c * 12288 + 128, k1 = c == 7 ? HEAD_BYTES : (c + 1) * 12288 + 128;
    mbar_expect_tx(bars + c * 8, 12288 + (k1 - k0));
    bulk_g2s(sK + k0, gq + 32 * HEAD_BYTES + k0, k1 - k0, bars + c * 8);
    bulk_g2s(sV + c * 12288, gq + 64 * HEAD_BYTES + c * 12288, 12288, bars + c * 8);
  };
  if (tid == 480) { load_kv(0); load_kv(1); }
  int next_kv = 2;
  if (tid == 0) TS(kid, 6);
  if (!__any_sync(0xffffffffu, bad)) {
  if (tid == 0) TS(kid, 7);
  if (tid == 0 && (q[0] ^ q[1] ^ q[2] ^ q[3] ^ q[4] ^ q[5]) != 0x12345u) TS(kid, 24);
#pragma unroll 1
  for (int tt = 0; tt < 2; tt++) {
    const int row0 = qt * 512 + (tt * 4 + wg) * 64 + warp * 16 + (lane >> 2);
    float S[64], O[12];
    uint32_t P[32];
#pragma unroll
    for (int k = 0; k < 12; k++) O[k] = 0.f;
#pragma unroll
    for (int k = 0; k < 64; k++) S[k] = 0.f;
    uint64_t gk = dK, gv = dV;
#pragma unroll 1
    for (int g = 0; g < 16; g++) {
      if (tid == 0 && tt == 0 && g < 1) TS(kid, 8 + g * 2);
      if ((g & 1) == 0) {
        if (next_kv < 8) { if (tid == 480) load_kv(next_kv); next_kv++; }
        mbar_wait(bars + (g >> 1) * 8, 0);
      }
      if (tid == 0 && tt == 0 && g < 1) TS(kid, 9 + g * 2);
      wg_fence();
      wgmma_rs_n128<0>(S, q[0], q[1], q[2], q[3], gk, 0);
      wgmma_rs_n128<0>(S, q[4], q[5], z0, z1, gk + 16, 1);
      wg_commit();
      wg_wait<0>();
      fence_regs(S);
#pragma unroll
      for (int b = 0; b < 16; b++) {
        if (is_mufu(b)) { P[2 * b] = pack_bf16(ex2(S[4 * b]), ex2(S[4 * b + 1])); P[2 * b + 1] = pack_bf16(ex2(S[4 * b + 2]), ex2(S[4 * b + 3])); }
        else { P[2 * b] = exp2_poly_pair(S[4 * b], S[4 * b + 1]); P[2 * b + 1] = exp2_poly_pair(S[4 * b + 2], S[4 * b + 3]); }
      }
      fence_regs(P);
      wg_fence();
#pragma unroll
      for (int s = 0; s < 8; s++) wgmma_rs_n24<1>(O, P[4 * s], P[4 * s + 1], P[4 * s + 2], P[4 * s + 3], gv + s * 48, 1);
      wg_commit();
      wg_wait<0>();
      gk += 384; gv += 384;
    }
    fence_regs(O);
    if (tid == 0) TS(kid, 2 + tt);
    load_q(1);
    att_store(O, row0, h, lane);
    float m = 0.f;
#pragma unroll
    for (int k = 0; k < 12; k++) { m = fmaxf(m, fabsf(O[k])); bad |= (O[k] != O[k]); }
    bad |= !(m <= 3e38f);
    if ((lane & 3) == 2) bad |= !(O[8] >= 0x1p-20f) || !(O[10] >= 0x1p-20f);
  }
  }
  if (tid == 0) TS(kid, 4);
  if (__syncthreads_or(bad)) {
    if (tid == 0) TS(kid, 5);
    if (tid == 480)
      for (; next_kv < 8; next_kv++) load_kv(next_kv);
    for (int c = 0; c < 8; c++) mbar_wait(bars + c * 8, 0);
#pragma unroll 1
    for (int tt = 0; tt < 2; tt++) {
      const int row0 = qt * 512 + (tt * 4 + wg) * 64 + warp * 16 + (lane >> 2);
      load_q(tt);
      if ((lane & 3) >= 2) { q[4] = 0u; q[5] = 0u; }
      float S[64], O[12], m0 = -INFINITY, m1 = -INFINITY;
      uint32_t P[32];
#pragma unroll
      for (int k = 0; k < 12; k++) O[k] = 0.f;
#pragma unroll
      for (int k = 0; k < 64; k++) S[k] = 0.f;
      uint64_t gk = dK, gv = dV;
#pragma unroll 1
      for (int g = 0; g < 16; g++) {
        wg_fence();
        wgmma_rs_n128<0>(S, q[0], q[1], q[2], q[3], gk, 0);
        wgmma_rs_n128<0>(S, q[4], q[5], z0, z1, gk + 16, 1);
        wg_commit();
        wg_wait<0>();
        fence_regs(S);
        float x0 = m0, x1 = m1;
#pragma unroll
        for (int b = 0; b < 16; b++) {
          if (!is_mufu(b)) { S[4 * b] *= 0x1p22f; S[4 * b + 1] *= 0x1p22f; S[4 * b + 2] *= 0x1p22f; S[4 * b + 3] *= 0x1p22f; }
          x0 = fmaxf(x0, fmaxf(S[4 * b], S[4 * b + 1]));
          x1 = fmaxf(x1, fmaxf(S[4 * b + 2], S[4 * b + 3]));
        }
        x0 = fmaxf(x0, __shfl_xor_sync(0xffffffffu, x0, 1)); x1 = fmaxf(x1, __shfl_xor_sync(0xffffffffu, x1, 1));
        x0 = fmaxf(x0, __shfl_xor_sync(0xffffffffu, x0, 2)); x1 = fmaxf(x1, __shfl_xor_sync(0xffffffffu, x1, 2));
        const float al0 = ex2(m0 - x0), al1 = ex2(m1 - x1);
        m0 = x0; m1 = x1;
#pragma unroll
        for (int c = 0; c < 3; c++) { O[4 * c] *= al0; O[4 * c + 1] *= al0; O[4 * c + 2] *= al1; O[4 * c + 3] *= al1; }
#pragma unroll
        for (int b = 0; b < 16; b++) {
          P[2 * b] = pack_bf16(ex2(S[4 * b] - m0), ex2(S[4 * b + 1] - m0));
          P[2 * b + 1] = pack_bf16(ex2(S[4 * b + 2] - m1), ex2(S[4 * b + 3] - m1));
        }
        fence_regs(P);
        fence_regs(O);
        wg_fence();
#pragma unroll
        for (int s = 0; s < 8; s++) wgmma_rs_n24<1>(O, P[4 * s], P[4 * s + 1], P[4 * s + 2], P[4 * s + 3], gv + s * 48, 1);
        wg_commit();
        wg_wait<0>();
        fence_regs(O);
        gk += 384; gv += 384;
      }
      att_store(O, row0, h, lane);
    }
  }
}

typedef CUresult (*EncodeFn)(CUtensorMap*, CUtensorMapDataType, cuuint32_t, void*, const cuuint64_t*, const cuuint64_t*, const cuuint32_t*,
                             const cuuint32_t*, CUtensorMapInterleave, CUtensorMapSwizzle, CUtensorMapL2promotion, CUtensorMapFloatOOBfill);

static void make_a(EncodeFn enc, CUtensorMap* m, const void* ptr, int K) {
  cuuint64_t dims[2] = {(cuuint64_t)K, (cuuint64_t)SEQ}, strides[1] = {(cuuint64_t)K * 2};
  cuuint32_t box[2] = {64, 128}, es[2] = {1, 1};
  enc(m, CU_TENSOR_MAP_DATA_TYPE_BFLOAT16, 2, (void*)ptr, dims, strides, box, es, CU_TENSOR_MAP_INTERLEAVE_NONE, CU_TENSOR_MAP_SWIZZLE_128B,
      CU_TENSOR_MAP_L2_PROMOTION_NONE, CU_TENSOR_MAP_FLOAT_OOB_FILL_NONE);
}
static void make_out(EncodeFn enc, CUtensorMap* m, void* ptr) {
  cuuint64_t dims[2] = {(cuuint64_t)DM, (cuuint64_t)SEQ}, strides[1] = {(cuuint64_t)DM * 2};
  cuuint32_t box[2] = {80, 64}, es[2] = {1, 1};
  enc(m, CU_TENSOR_MAP_DATA_TYPE_BFLOAT16, 2, ptr, dims, strides, box, es, CU_TENSOR_MAP_INTERLEAVE_NONE, CU_TENSOR_MAP_SWIZZLE_NONE,
      CU_TENSOR_MAP_L2_PROMOTION_NONE, CU_TENSOR_MAP_FLOAT_OOB_FILL_NONE);
}
static void make_b(EncodeFn enc, CUtensorMap* m, const void* ptr, int K, int N, int BN, int bk, int bw) {
  cuuint64_t dims[3] = {(cuuint64_t)BN, (cuuint64_t)(N / BN), (cuuint64_t)K}, strides[2] = {(cuuint64_t)BN * 2, (cuuint64_t)N * 2};
  cuuint32_t box[3] = {(cuuint32_t)bw, 1, (cuuint32_t)bk}, es[3] = {1, 1, 1};
  enc(m, CU_TENSOR_MAP_DATA_TYPE_BFLOAT16, 3, (void*)ptr, dims, strides, box, es, CU_TENSOR_MAP_INTERLEAVE_NONE, bw == 64 ? CU_TENSOR_MAP_SWIZZLE_128B : CU_TENSOR_MAP_SWIZZLE_32B,
      CU_TENSOR_MAP_L2_PROMOTION_NONE, CU_TENSOR_MAP_FLOAT_OOB_FILL_NONE);
}
template <typename... KArgs, typename... Args>
static void launch(void (*kern)(KArgs...), int grid, int threads, int smem, bool pdl, Args... args) {
  cudaFuncSetAttribute(kern, cudaFuncAttributeMaxDynamicSharedMemorySize, smem);
  cudaLaunchConfig_t cfg = {};
  cfg.gridDim = dim3(grid); cfg.blockDim = dim3(threads); cfg.dynamicSmemBytes = smem; cfg.stream = cudaStreamPerThread;
  cudaLaunchAttribute at[1];
  at[0].id = cudaLaunchAttributeProgrammaticStreamSerialization; at[0].val.programmaticStreamSerializationAllowed = 1;
  cfg.attrs = at; cfg.numAttrs = pdl ? 1 : 0;
  cudaLaunchKernelEx(&cfg, kern, KArgs(args)...);
}

static void make_pref(signed char* pref, int ntpc) {
  auto kern = chain_kernel<PH_WO | PH_W1 | PH_W2, false, true>;
  cudaFuncSetAttribute(kern, cudaFuncAttributeMaxDynamicSharedMemorySize, CHAIN_SMEM);
  cudaFuncSetAttribute(kern, cudaFuncAttributeNonPortableClusterSizeAllowed, 1);
  int n[10] = {0};
  for (int t = 2; t <= 8; t++) {
    cudaLaunchConfig_t cfg = {};
    cfg.gridDim = dim3(2 * t * 16); cfg.blockDim = dim3(CHAIN_THREADS); cfg.dynamicSmemBytes = CHAIN_SMEM;
    cudaLaunchAttribute at[1];
    at[0].id = cudaLaunchAttributeClusterDimension; at[0].val.clusterDim.x = 2 * t; at[0].val.clusterDim.y = 1; at[0].val.clusterDim.z = 1;
    cfg.attrs = at; cfg.numAttrs = 1;
    if (cudaOccupancyMaxActiveClusters(&n[t], kern, &cfg) != cudaSuccess) { n[t] = -1; cudaGetLastError(); }
  }
  int best[10] = {0}, cnt[10], found = 0;
  for (int code = 0; code < 1000000 && !found; code++) {
    int c = code, tot = 0, g = 0;
    for (int m = 0; m < 10; m++) cnt[m] = 0;
    for (int m = 4; m <= 9; m++) { cnt[m] = c % 10; c /= 10; tot += cnt[m] * m; g += cnt[m]; }
    if (g > 9 || tot > ntpc) continue;
    bool ok = true;
    for (int t = 3; t <= 8 && ok; t++) { int s = 0; for (int m = 4; m <= 9; m++) s += cnt[m] * (m / t); ok = (s == n[t]); }
    if (ok) { found = 1; for (int m = 0; m < 10; m++) best[m] = cnt[m]; }
  }
  int grp[80], size[10], ng = 0, id = 0;
  for (int t = 0; t < 80; t++) { grp[t] = -1; pref[2 * t] = pref[2 * t + 1] = -1; }
  if (found) {
    for (int m = 4; m <= 9; m++) for (int k = 0; k < best[m]; k++) size[ng++] = m;
    for (int r = 0; r < 9; r++) for (int g = 0; g < ng; g++) if (size[g] > r && id < ntpc) grp[id++] = g;
  }
  int nb = 0;
  bool used[80] = {false};
  auto put = [&](int t, int blk, int w) {
    const int tile = blk * 16 + w * 2;
    pref[2 * t] = (signed char)tile; pref[2 * t + 1] = (signed char)(tile + 1); used[t] = true;
  };
  for (int g = 0; g < ng && nb < 8; g++)
    if (size[g] >= 8) {
      int w = 0;
      for (int t = 0; t < ntpc && w < 8; t++) if (grp[t] == g) put(t, nb, w++);
      nb++;
    }
  int pos = nb * 8;
  for (int pass = 0; pass < 2; pass++)
    for (int g = 0; g <= ng; g++)
      for (int t = 0; t < ntpc && pos < 64; t++)
        if (!used[t] && (g < ng ? (grp[t] == g && (size[g] < 8) == (pass == 0)) : (pass == 1 && grp[t] < 0))) { put(t, pos >> 3, pos & 7); pos++; }
}

extern "C" void kernel_launch(void* const* d_in, const int* in_sizes, int n_in, void* d_out, int out_size) {
  const bf16* x = (const bf16*)d_in[0];
  const bf16* wqkv = (const bf16*)d_in[1];
  const bf16* wo = (const bf16*)d_in[2];
  const bf16* w1 = (const bf16*)d_in[4];
  const bf16* b1 = (const bf16*)d_in[5];
  const bf16* w2 = (const bf16*)d_in[6];
  const bf16* b2 = (const bf16*)d_in[7];
  void* fn = nullptr;
  cudaDriverEntryPointQueryResult qr;
  cudaGetDriverEntryPoint("cuTensorMapEncodeTiled", &fn, cudaEnableDefault, &qr);
  EncodeFn enc = (EncodeFn)fn;
  void *px0, *px2, *pf, *pz;
  cudaGetSymbolAddress(&px0, g_x0);
  cudaGetSymbolAddress(&px2, g_x2); cudaGetSymbolAddress(&pf, g_s);
  unsigned int* flags = ((Small*)pf)->flags;
  pz = ((Small*)pf)->zeros;

  int nsm = 132;
  cudaDeviceGetAttribute(&nsm, cudaDevAttrMultiProcessorCount, 0);
  const int ngrid = nsm >= 128 ? (nsm > 160 ? 160 : (nsm & ~1)) : 128;
  ChainParams p;
  make_pref(p.pref, ngrid / 2);
  make_a(enc, &p.a_x, x, DM);
  make_out(enc, &p.o_out, d_out);
  make_b(enc, &p.b_wo, wo, DM, DM, 80, 64, 16); make_b(enc, &p.b_w1, w1, DM, FF, 216, 64, 16); make_b(enc, &p.b_w2, w2, FF, DM, 80, 96, 16);
  make_b(enc, &p.b_wqkv, wqkv, DM, 1920, 120, 64, 64);
  p.xres = (const bf16*)px0; p.xin = x; p.b1 = b1; p.b2 = b2; p.flags = flags; p.kid = 0;

  launch(chain_kernel<PH_QKV, true, false>, ngrid, CHAIN_THREADS, CHAIN_SMEM, false, p);
  launch(att_kernel, 128, 512, ATT_SMEM, true, flags + NORM_OFF, flags, flags + FLAG_SET + NORM_OFF, flags + 2 * FLAG_SET, (const uint32_t*)pz, 1);
  p.flags = flags + FLAG_SET; p.kid = 2;
  launch(chain_kernel<PH_WO | PH_W1 | PH_W2 | PH_QKV, false, false>, ngrid, CHAIN_THREADS, CHAIN_SMEM, true, p);
  launch(att_kernel, 128, 512, ATT_SMEM, true, flags + FLAG_SET + NORM_OFF, flags + FLAG_SET, flags + NORM_OFF, (unsigned int*)nullptr, (const uint32_t*)pz, 3);
  p.kid = 4; p.xres = (const bf16*)px2; p.flags = flags + 2 * FLAG_SET;
  launch(chain_kernel<PH_WO | PH_W1 | PH_W2, false, true>, ngrid, CHAIN_THREADS, CHAIN_SMEM, true, p);
}
```

```cpp
#include <cuda_runtime.h>
#include <cuda_bf16.h>
#include <cuda.h>
#include <stdint.h>

#define NSPLIT 8
#define QSPLIT 0
#define BL0 4
#define BL1 2
#define BL2 2
#define BL3 2
#define KLIM 4
#define MUFUM 0x4949u
typedef __nv_bfloat16 bf16;

constexpr int SEQ = 2048, DM = 640, FF = 1728;
constexpr float LN_EPS = 1e-5f;
constexpr int HEAD_BYTES = 98304;
constexpr uint32_t MUFU_MASK = MUFUM;
__host__ __device__ constexpr bool is_mufu(int g) { return (MUFU_MASK >> (g & 15)) & 1u; }

__device__ __align__(1024) bf16 g_qkv[96 * (HEAD_BYTES / 2)];
constexpr int WT_WO = 0, WT_W1 = WT_WO + 80 * 10240, WT_W2 = WT_W1 + 160 * 14336, WT_QKV = WT_W2 + 144 * 15360, WT_END = WT_QKV + 160 * 16384;
__device__ __align__(1024) uint8_t g_wt[WT_END];
__device__ __forceinline__ int x_line(int row, int cg) { return (((row >> 7) * 10 + (cg >> 3)) * 16 + ((row >> 3) & 15)) * 8 + (cg & 7); }
__device__ __forceinline__ int o_line(int row, int cg) { return (((row >> 6) * 10 + (cg >> 3)) * 8 + ((row >> 3) & 7)) * 8 + (cg & 7); }
__device__ __forceinline__ int h_line(int row, int cg) { return (((row >> 6) * 18 + cg / 12) * 8 + ((row >> 3) & 7)) * 12 + cg % 12; }
__device__ __align__(1024) bf16 g_x0[SEQ * DM];
__device__ __align__(1024) bf16 g_o[SEQ * DM];
__device__ __align__(1024) bf16 g_x1[SEQ * DM];
__device__ __align__(1024) bf16 g_x2[SEQ * DM];
__device__ __align__(1024) bf16 g_h[SEQ * FF];
constexpr int FLAG_SET = 320, NORM_OFF = 256;
struct Small {
  float2 st0[2 * SEQ];
  float2 st1[8 * SEQ];
  float2 st2[8 * SEQ];
  float csp_w1[10 * 1792];
  float cs_qkv[1920];
  unsigned int flags[3 * FLAG_SET];
  uint32_t zeros[4];
};
__device__ __align__(1024) Small g_s;

#define TS(k, s) do {} while (0)
#define DBG(x)
__device__ __forceinline__ uint32_t smem_u32(const void* p) { return (uint32_t)__cvta_generic_to_shared(p); }
__device__ __forceinline__ void mbar_init(uint32_t bar, int cnt) { asm volatile("mbarrier.init.shared::cta.b64 [%0], %1;" ::"r"(bar), "r"(cnt) : "memory"); }
__device__ __forceinline__ void mbar_expect_tx(uint32_t bar, uint32_t bytes) { asm volatile("mbarrier.arrive.expect_tx.shared::cta.b64 _, [%0], %1;" ::"r"(bar), "r"(bytes) : "memory"); }
__device__ __forceinline__ void mbar_arrive(uint32_t bar) { asm volatile("mbarrier.arrive.shared::cta.b64 _, [%0];" ::"r"(bar) : "memory"); }
__device__ __forceinline__ bool mbar_try(uint32_t bar, uint32_t parity) {
  uint32_t ok;
  asm volatile("{\n.reg .pred p;\nmbarrier.try_wait.parity.shared::cta.b64 p, [%1], %2;\nselp.u32 %0, 1, 0, p;\n}\n" : "=r"(ok) : "r"(bar), "r"(parity) : "memory");
  return ok != 0;
}
__device__ __forceinline__ bool mbar_test(uint32_t bar, uint32_t parity) {
  uint32_t ok;
  asm volatile("{\n.reg .pred p;\nmbarrier.test_wait.parity.shared::cta.b64 p, [%1], %2;\nselp.u32 %0, 1, 0, p;\n}\n" : "=r"(ok) : "r"(bar), "r"(parity) : "memory");
  return ok != 0;
}
__device__ __forceinline__ void mbar_wait(uint32_t bar, uint32_t parity) {
  if (mbar_try(bar, parity)) return;
#pragma unroll 1
  for (int it = 0; it < (1 << 22); it++)
    if (mbar_try(bar, parity)) return;
  __trap();
}
__device__ __forceinline__ void mbar_wait_warp(uint32_t bar, uint32_t parity) {
#pragma unroll 1
  for (int it = 0; !__all_sync(0xffffffffu, mbar_try(bar, parity)); it++)
    if (it > (1 << 22)) __trap();
}
__device__ __forceinline__ void flag_wait(const unsigned int* f, unsigned int target) {
  unsigned int v;
#pragma unroll 1
  for (int it = 0; it < (1 << 22); it++) {
    asm volatile("ld.acquire.gpu.global.u32 %0, [%1];" : "=r"(v) : "l"(f) : "memory");
    if (v >= target) return;
  }
  __trap();
}
__device__ __forceinline__ void flag_signal(unsigned int* f) { asm volatile("red.release.gpu.global.add.u32 [%0], 1;" ::"l"(f) : "memory"); }
__device__ __forceinline__ void fence_async_global() { asm volatile("fence.proxy.async.global;" ::: "memory"); }
__device__ __forceinline__ void pdl_wait() { asm volatile("griddepcontrol.wait;" ::: "memory"); }
__device__ __forceinline__ void pdl_launch() { asm volatile("griddepcontrol.launch_dependents;" ::: "memory"); }
__device__ __forceinline__ void named_bar(int id, int n) { asm volatile("bar.sync %0, %1;" ::"r"(id), "r"(n) : "memory"); }
__device__ __forceinline__ void bulk_g2s(uint32_t dst, const void* src, uint32_t bytes, uint32_t bar) {
  asm volatile("cp.async.bulk.shared::cluster.global.mbarrier::complete_tx::bytes [%0], [%1], %2, [%3];" ::"r"(dst), "l"(src), "r"(bytes), "r"(bar) : "memory");
}
__device__ __forceinline__ void prefetch_l2(const void* src, uint32_t bytes) { asm volatile("cp.async.bulk.prefetch.L2.global [%0], %1;" ::"l"(src), "r"(bytes) : "memory"); }
__device__ __forceinline__ void tma_2d(uint32_t dst, const CUtensorMap* m, int c0, int c1, uint32_t bar) {
  asm volatile("cp.async.bulk.tensor.2d.shared::cluster.global.mbarrier::complete_tx::bytes [%0], [%1, {%3, %4}], [%2];" ::"r"(dst), "l"(m), "r"(bar), "r"(c0), "r"(c1) : "memory");
}
__device__ __forceinline__ void tma_3d(uint32_t dst, const CUtensorMap* m, int c0, int c1, int c2, uint32_t bar) {
  asm volatile("cp.async.bulk.tensor.3d.shared::cluster.global.mbarrier::complete_tx::bytes [%0], [%1, {%3, %4, %5}], [%2];" ::"r"(dst), "l"(m), "r"(bar), "r"(c0), "r"(c1), "r"(c2) : "memory");
}
__device__ __forceinline__ void prefetch_map(const CUtensorMap* m) { asm volatile("prefetch.tensormap [%0];" ::"l"(m) : "memory"); }
__device__ __forceinline__ void wg_fence() { asm volatile("wgmma.fence.sync.aligned;" ::: "memory"); }
__device__ __forceinline__ void wg_commit() { asm volatile("wgmma.commit_group.sync.aligned;" ::: "memory"); }
template <int N> __device__ __forceinline__ void wg_wait() { asm volatile("wgmma.wait_group.sync.aligned %0;" ::"n"(N) : "memory"); }
template <int N> __device__ __forceinline__ void fence_regs(float (&d)[N]) {
#pragma unroll
  for (int i = 0; i < N; i++) asm volatile("" : "+f"(d[i])::"memory");
}
template <int N> __device__ __forceinline__ void fence_regs(uint32_t (&d)[N]) {
#pragma unroll
  for (int i = 0; i < N; i++) asm volatile("" : "+r"(d[i])::"memory");
}
__device__ __forceinline__ uint64_t mk_desc(uint32_t addr, uint32_t lbo, uint32_t sbo, uint64_t swz) {
  return (uint64_t)((addr & 0x3FFFF) >> 4) | ((uint64_t)(lbo >> 4) << 16) | ((uint64_t)(sbo >> 4) << 32) | (swz << 62);
}
__device__ __forceinline__ uint32_t pack_bf16(float lo, float hi) {
  uint32_t r;
  asm("cvt.rn.bf16x2.f32 %0, %1, %2;" : "=r"(r) : "f"(hi), "f"(lo));
  return r;
}
__device__ __forceinline__ float bf_lo(uint32_t v) { return __uint_as_float(v << 16); }
__device__ __forceinline__ float bf_hi(uint32_t v) { return __uint_as_float(v & 0xFFFF0000u); }
__device__ __forceinline__ float ex2(float x) { float r; asm("ex2.approx.ftz.f32 %0, %1;" : "=f"(r) : "f"(x)); return r; }

template<int TB> __device__ __forceinline__ void wgmma_rs_n24(float (&d)[12], uint32_t a0, uint32_t a1, uint32_t a2, uint32_t a3, uint64_t db, int sd) {
  asm volatile("{\n.reg .pred p;\nsetp.ne.b32 p, %17, 0;\n"
    "wgmma.mma_async.sync.aligned.m64n24k16.f32.bf16.bf16 "
    "{%0,%1,%2,%3,%4,%5,%6,%7,%8,%9,%10,%11}, "
    "{%12,%13,%14,%15}, %16, p, 1, 1, %18;\n}\n"
    : "+f"(d[0]),"+f"(d[1]),"+f"(d[2]),"+f"(d[3]),"+f"(d[4]),"+f"(d[5]),"+f"(d[6]),"+f"(d[7]),"+f"(d[8]),"+f"(d[9]),"+f"(d[10]),"+f"(d[11])
    : "r"(a0), "r"(a1), "r"(a2), "r"(a3), "l"(db), "r"(sd), "n"(TB));
}
template<int TB> __device__ __forceinline__ void wgmma_rs_n64(float (&d)[32], uint32_t a0, uint32_t a1, uint32_t a2, uint32_t a3, uint64_t db, int sd) {
  asm volatile("{\n.reg .pred p;\nsetp.ne.b32 p, %37, 0;\n"
    "wgmma.mma_async.sync.aligned.m64n64k16.f32.bf16.bf16 "
    "{%0,%1,%2,%3,%4,%5,%6,%7,%8,%9,%10,%11,%12,%13,%14,%15,%16,%17,%18,%19,%20,%21,%22,%23,%24,%25,%26,%27,%28,%29,%30,%31}, "
    "{%32,%33,%34,%35}, %36, p, 1, 1, %38;\n}\n"
    : "+f"(d[0]),"+f"(d[1]),"+f"(d[2]),"+f"(d[3]),"+f"(d[4]),"+f"(d[5]),"+f"(d[6]),"+f"(d[7]),"+f"(d[8]),"+f"(d[9]),"+f"(d[10]),"+f"(d[11]),"+f"(d[12]),"+f"(d[13]),"+f"(d[14]),"+f"(d[15]),"+f"(d[16]),"+f"(d[17]),"+f"(d[18]),"+f"(d[19]),"+f"(d[20]),"+f"(d[21]),"+f"(d[22]),"+f"(d[23]),"+f"(d[24]),"+f"(d[25]),"+f"(d[26]),"+f"(d[27]),"+f"(d[28]),"+f"(d[29]),"+f"(d[30]),"+f"(d[31])
    : "r"(a0), "r"(a1), "r"(a2), "r"(a3), "l"(db), "r"(sd), "n"(TB));
}
template<int TB> __device__ __forceinline__ void wgmma_rs_n120(float (&d)[60], uint32_t a0, uint32_t a1, uint32_t a2, uint32_t a3, uint64_t db, int sd) {
  asm volatile("{\n.reg .pred p;\nsetp.ne.b32 p, %65, 0;\n"
    "wgmma.mma_async.sync.aligned.m64n120k16.f32.bf16.bf16 "
    "{%0,%1,%2,%3,%4,%5,%6,%7,%8,%9,%10,%11,%12,%13,%14,%15,%16,%17,%18,%19,%20,%21,%22,%23,%24,%25,%26,%27,%28,%29,%30,%31,%32,%33,%34,%35,%36,%37,%38,%39,%40,%41,%42,%43,%44,%45,%46,%47,%48,%49,%50,%51,%52,%53,%54,%55,%56,%57,%58,%59}, "
    "{%60,%61,%62,%63}, %64, p, 1, 1, %66;\n}\n"
    : "+f"(d[0]),"+f"(d[1]),"+f"(d[2]),"+f"(d[3]),"+f"(d[4]),"+f"(d[5]),"+f"(d[6]),"+f"(d[7]),"+f"(d[8]),"+f"(d[9]),"+f"(d[10]),"+f"(d[11]),"+f"(d[12]),"+f"(d[13]),"+f"(d[14]),"+f"(d[15]),"+f"(d[16]),"+f"(d[17]),"+f"(d[18]),"+f"(d[19]),"+f"(d[20]),"+f"(d[21]),"+f"(d[22]),"+f"(d[23]),"+f"(d[24]),"+f"(d[25]),"+f"(d[26]),"+f"(d[27]),"+f"(d[28]),"+f"(d[29]),"+f"(d[30]),"+f"(d[31]),"+f"(d[32]),"+f"(d[33]),"+f"(d[34]),"+f"(d[35]),"+f"(d[36]),"+f"(d[37]),"+f"(d[38]),"+f"(d[39]),"+f"(d[40]),"+f"(d[41]),"+f"(d[42]),"+f"(d[43]),"+f"(d[44]),"+f"(d[45]),"+f"(d[46]),"+f"(d[47]),"+f"(d[48]),"+f"(d[49]),"+f"(d[50]),"+f"(d[51]),"+f"(d[52]),"+f"(d[53]),"+f"(d[54]),"+f"(d[55]),"+f"(d[56]),"+f"(d[57]),"+f"(d[58]),"+f"(d[59])
    : "r"(a0), "r"(a1), "r"(a2), "r"(a3), "l"(db), "r"(sd), "n"(TB));
}
template<int TB> __device__ __forceinline__ void wgmma_rs_n128(float (&d)[64], uint32_t a0, uint32_t a1, uint32_t a2, uint32_t a3, uint64_t db, int sd) {
  asm volatile("{\n.reg .pred p;\nsetp.ne.b32 p, %69, 0;\n"
    "wgmma.mma_async.sync.aligned.m64n128k16.f32.bf16.bf16 "
    "{%0,%1,%2,%3,%4,%5,%6,%7,%8,%9,%10,%11,%12,%13,%14,%15,%16,%17,%18,%19,%20,%21,%22,%23,%24,%25,%26,%27,%28,%29,%30,%31,%32,%33,%34,%35,%36,%37,%38,%39,%40,%41,%42,%43,%44,%45,%46,%47,%48,%49,%50,%51,%52,%53,%54,%55,%56,%57,%58,%59,%60,%61,%62,%63}, "
    "{%64,%65,%66,%67}, %68, p, 1, 1, %70;\n}\n"
    : "+f"(d[0]),"+f"(d[1]),"+f"(d[2]),"+f"(d[3]),"+f"(d[4]),"+f"(d[5]),"+f"(d[6]),"+f"(d[7]),"+f"(d[8]),"+f"(d[9]),"+f"(d[10]),"+f"(d[11]),"+f"(d[12]),"+f"(d[13]),"+f"(d[14]),"+f"(d[15]),"+f"(d[16]),"+f"(d[17]),"+f"(d[18]),"+f"(d[19]),"+f"(d[20]),"+f"(d[21]),"+f"(d[22]),"+f"(d[23]),"+f"(d[24]),"+f"(d[25]),"+f"(d[26]),"+f"(d[27]),"+f"(d[28]),"+f"(d[29]),"+f"(d[30]),"+f"(d[31]),"+f"(d[32]),"+f"(d[33]),"+f"(d[34]),"+f"(d[35]),"+f"(d[36]),"+f"(d[37]),"+f"(d[38]),"+f"(d[39]),"+f"(d[40]),"+f"(d[41]),"+f"(d[42]),"+f"(d[43]),"+f"(d[44]),"+f"(d[45]),"+f"(d[46]),"+f"(d[47]),"+f"(d[48]),"+f"(d[49]),"+f"(d[50]),"+f"(d[51]),"+f"(d[52]),"+f"(d[53]),"+f"(d[54]),"+f"(d[55]),"+f"(d[56]),"+f"(d[57]),"+f"(d[58]),"+f"(d[59]),"+f"(d[60]),"+f"(d[61]),"+f"(d[62]),"+f"(d[63])
    : "r"(a0), "r"(a1), "r"(a2), "r"(a3), "l"(db), "r"(sd), "n"(TB));
}
__device__ __forceinline__ void wgmma_ss(float (&d)[40], uint64_t da, uint64_t db, int sd) {
  asm volatile("{\n.reg .pred p;\nsetp.ne.b32 p, %42, 0;\n"
    "wgmma.mma_async.sync.aligned.m64n80k16.f32.bf16.bf16 "
    "{%0,%1,%2,%3,%4,%5,%6,%7,%8,%9,%10,%11,%12,%13,%14,%15,%16,%17,%18,%19,%20,%21,%22,%23,%24,%25,%26,%27,%28,%29,%30,%31,%32,%33,%34,%35,%36,%37,%38,%39}, "
    "%40, %41, p, 1, 1, 0, 1;\n}\n"
    : "+f"(d[0]),"+f"(d[1]),"+f"(d[2]),"+f"(d[3]),"+f"(d[4]),"+f"(d[5]),"+f"(d[6]),"+f"(d[7]),"+f"(d[8]),"+f"(d[9]),"+f"(d[10]),"+f"(d[11]),"+f"(d[12]),"+f"(d[13]),"+f"(d[14]),"+f"(d[15]),"+f"(d[16]),"+f"(d[17]),"+f"(d[18]),"+f"(d[19]),"+f"(d[20]),"+f"(d[21]),"+f"(d[22]),"+f"(d[23]),"+f"(d[24]),"+f"(d[25]),"+f"(d[26]),"+f"(d[27]),"+f"(d[28]),"+f"(d[29]),"+f"(d[30]),"+f"(d[31]),"+f"(d[32]),"+f"(d[33]),"+f"(d[34]),"+f"(d[35]),"+f"(d[36]),"+f"(d[37]),"+f"(d[38]),"+f"(d[39])
    : "l"(da), "l"(db), "r"(sd));
}
__device__ __forceinline__ void wgmma_ss(float (&d)[56], uint64_t da, uint64_t db, int sd) {
  asm volatile("{\n.reg .pred p;\nsetp.ne.b32 p, %58, 0;\n"
    "wgmma.mma_async.sync.aligned.m64n112k16.f32.bf16.bf16 "
    "{%0,%1,%2,%3,%4,%5,%6,%7,%8,%9,%10,%11,%12,%13,%14,%15,%16,%17,%18,%19,%20,%21,%22,%23,%24,%25,%26,%27,%28,%29,%30,%31,%32,%33,%34,%35,%36,%37,%38,%39,%40,%41,%42,%43,%44,%45,%46,%47,%48,%49,%50,%51,%52,%53,%54,%55}, "
    "%56, %57, p, 1, 1, 0, 1;\n}\n"
    : "+f"(d[0]),"+f"(d[1]),"+f"(d[2]),"+f"(d[3]),"+f"(d[4]),"+f"(d[5]),"+f"(d[6]),"+f"(d[7]),"+f"(d[8]),"+f"(d[9]),"+f"(d[10]),"+f"(d[11]),"+f"(d[12]),"+f"(d[13]),"+f"(d[14]),"+f"(d[15]),"+f"(d[16]),"+f"(d[17]),"+f"(d[18]),"+f"(d[19]),"+f"(d[20]),"+f"(d[21]),"+f"(d[22]),"+f"(d[23]),"+f"(d[24]),"+f"(d[25]),"+f"(d[26]),"+f"(d[27]),"+f"(d[28]),"+f"(d[29]),"+f"(d[30]),"+f"(d[31]),"+f"(d[32]),"+f"(d[33]),"+f"(d[34]),"+f"(d[35]),"+f"(d[36]),"+f"(d[37]),"+f"(d[38]),"+f"(d[39]),"+f"(d[40]),"+f"(d[41]),"+f"(d[42]),"+f"(d[43]),"+f"(d[44]),"+f"(d[45]),"+f"(d[46]),"+f"(d[47]),"+f"(d[48]),"+f"(d[49]),"+f"(d[50]),"+f"(d[51]),"+f"(d[52]),"+f"(d[53]),"+f"(d[54]),"+f"(d[55])
    : "l"(da), "l"(db), "r"(sd));
}
__device__ __forceinline__ void wgmma_ss(float (&d)[60], uint64_t da, uint64_t db, int sd) {
  asm volatile("{\n.reg .pred p;\nsetp.ne.b32 p, %62, 0;\n"
    "wgmma.mma_async.sync.aligned.m64n120k16.f32.bf16.bf16 "
    "{%0,%1,%2,%3,%4,%5,%6,%7,%8,%9,%10,%11,%12,%13,%14,%15,%16,%17,%18,%19,%20,%21,%22,%23,%24,%25,%26,%27,%28,%29,%30,%31,%32,%33,%34,%35,%36,%37,%38,%39,%40,%41,%42,%43,%44,%45,%46,%47,%48,%49,%50,%51,%52,%53,%54,%55,%56,%57,%58,%59}, "
    "%60, %61, p, 1, 1, 0, 1;\n}\n"
    : "+f"(d[0]),"+f"(d[1]),"+f"(d[2]),"+f"(d[3]),"+f"(d[4]),"+f"(d[5]),"+f"(d[6]),"+f"(d[7]),"+f"(d[8]),"+f"(d[9]),"+f"(d[10]),"+f"(d[11]),"+f"(d[12]),"+f"(d[13]),"+f"(d[14]),"+f"(d[15]),"+f"(d[16]),"+f"(d[17]),"+f"(d[18]),"+f"(d[19]),"+f"(d[20]),"+f"(d[21]),"+f"(d[22]),"+f"(d[23]),"+f"(d[24]),"+f"(d[25]),"+f"(d[26]),"+f"(d[27]),"+f"(d[28]),"+f"(d[29]),"+f"(d[30]),"+f"(d[31]),"+f"(d[32]),"+f"(d[33]),"+f"(d[34]),"+f"(d[35]),"+f"(d[36]),"+f"(d[37]),"+f"(d[38]),"+f"(d[39]),"+f"(d[40]),"+f"(d[41]),"+f"(d[42]),"+f"(d[43]),"+f"(d[44]),"+f"(d[45]),"+f"(d[46]),"+f"(d[47]),"+f"(d[48]),"+f"(d[49]),"+f"(d[50]),"+f"(d[51]),"+f"(d[52]),"+f"(d[53]),"+f"(d[54]),"+f"(d[55]),"+f"(d[56]),"+f"(d[57]),"+f"(d[58]),"+f"(d[59])
    : "l"(da), "l"(db), "r"(sd));
}

constexpr int PH_WO = 1, PH_W1 = 2, PH_W2 = 4, PH_QKV = 8;
constexpr int SA = 4, SB = 10, STAGE = 16384;
constexpr int SM_B = SA * STAGE;
constexpr int SM_CS = SM_B + SB * STAGE;
constexpr int SM_B1 = SM_CS + 448;
constexpr int SM_ROW = SM_B1 + 224;
constexpr int SM_BAR = SM_ROW + 2048;
constexpr int CHAIN_SMEM = SM_BAR + 344;
static_assert(CHAIN_SMEM <= 232448, "shared memory");
constexpr int CHAIN_THREADS = 352;
constexpr int BAR_FA = 0, BAR_EA = SA * 8, BAR_FB = 2 * SA * 8, BAR_EB = (2 * SA + SB) * 8, BAR_AUX = (2 * SA + 2 * SB) * 8, BAR_JOB = BAR_AUX + 32,
              BAR_FH = BAR_JOB, BAR_EH = BAR_JOB + 40, BAR_TILE = BAR_JOB + 80;

struct alignas(64) ChainParams {
  CUtensorMap a_x, b_wo, b_w1, b_wqkv, o_out;
  const bf16* xres;
  const bf16* xin;
  const bf16 *b1, *b2;
  unsigned int* flags;
  int kid;
  signed char pref[160];
};

template <int V> struct IC { static constexpr int value = V; };
struct Ring { uint32_t s, ph; };
template <int N> __device__ __forceinline__ void ring_adv(Ring& r) { if (++r.s == N) { r.s = 0; r.ph ^= 1; } }

template <int KT, int BYTES, int N, int STRIDE = STAGE, int LIM = 0>
__device__ __forceinline__ void produce(const void* src, uint32_t dst, uint32_t full, uint32_t empty, Ring& r) {
#pragma unroll 1
  for (int kt = 0; kt < KT; kt++) {
    if constexpr (LIM > 0) mbar_wait(full + (r.s >= LIM ? r.s - LIM : r.s + N - LIM) * 8, r.s >= LIM ? r.ph : r.ph ^ 1);
    mbar_wait(empty + r.s * 8, r.ph ^ 1);
    mbar_expect_tx(full + r.s * 8, BYTES);
    bulk_g2s(dst + r.s * STRIDE, (const uint8_t*)src + kt * BYTES, BYTES, full + r.s * 8);
    ring_adv<N>(r);
  }
}
template <int BYTES> __device__ __forceinline__ void produce_first(const void* src, uint32_t dst, uint32_t full, uint32_t empty, Ring& r) {
  produce<BL0, BYTES, SB>(src, dst, full, empty, r);
  produce<10 - BL0, BYTES, SB, STAGE, BL0>((const uint8_t*)src + BL0 * BYTES, dst, full, empty, r);
}
__device__ __forceinline__ void bulk_s2g(void* dst, uint32_t src, uint32_t bytes) {
  asm volatile("cp.async.bulk.global.shared::cta.bulk_group [%0], [%1], %2;\ncp.async.bulk.commit_group;" ::"l"(dst), "r"(src), "r"(bytes) : "memory");
}
template <int BK, bool B128> __device__ __forceinline__ uint64_t b_desc(uint32_t addr) { return B128 ? mk_desc(addr, 8192, 1024, 1) : mk_desc(addr, BK * 32, 256, 3); }

template <int BN, int MT, int KT, int BK, int APT, bool TILED, bool B128, bool HR = false>
__device__ __forceinline__ void mainloop(float (&acc)[MT][BN / 2], uint32_t sbase, uint32_t bars, int lane, int wg, int a0, bool pass, Ring& rb, int cont = 0, int dbgk = -1) {
  constexpr int NA = HR ? 5 : SA, AST = HR ? 12288 : STAGE, FA = HR ? BAR_FH : BAR_FA, EA = HR ? BAR_EH : BAR_EA;
  Ring ra{(uint32_t)a0 % NA, ((uint32_t)a0 / NA) & 1};
  if (HR || a0 != 0) named_bar(6 - wg, 256);
  DBG(long long cs0 = clock64();)
  mbar_wait(bars + BAR_FB + rb.s * 8, rb.ph);
  mbar_wait(bars + FA + ra.s * 8, ra.ph);
  DBG(long long wf = clock64() - cs0;)
  const uint64_t da0 = TILED ? mk_desc(sbase, 128, BK * 16, 0) : mk_desc(sbase, 16, 1024, 1), db0 = b_desc<BK, B128>(sbase + SM_B);
  uint32_t relA = 0, relB = 0;
#pragma unroll 1
  for (int kt = 0; kt < KT; kt += APT) {
#pragma unroll
    for (int u = 0; u < APT; u++) {
      const bool more = u + 1 < APT || kt + APT < KT;
      if (!more && pass) asm volatile("bar.arrive %0, 256;" ::"r"(5 + wg) : "memory");
      const uint64_t da = da0 + ra.s * (AST / 16) + u * 512, db = db0 + rb.s * (STAGE / 16);
      wg_fence();
#pragma unroll
      for (int k = 0; k < BK / 16; k++)
#pragma unroll
        for (int m = 0; m < MT; m++) wgmma_ss(acc[m], da + m * 512 + k * (TILED ? 16 : 2), db + k * (B128 ? 128 : 32), (kt | u | k | cont) != 0);
      wg_commit();
      const uint32_t curA = u == APT - 1 ? bars + EA + ra.s * 8 : 0, curB = bars + BAR_EB + rb.s * 8;
      if (u == APT - 1) ring_adv<NA>(ra);
      ring_adv<SB>(rb);
      bool ok = mbar_test(bars + BAR_FB + rb.s * 8, rb.ph);
      if (u == APT - 1) ok &= mbar_test(bars + FA + ra.s * 8, ra.ph);
      wg_wait<1>();
      if (lane == 0 && relB) { if (relA) mbar_arrive(relA); mbar_arrive(relB); }
      relA = curA; relB = curB;
      if (!ok && more) { mbar_wait(bars + BAR_FB + rb.s * 8, rb.ph); mbar_wait(bars + FA + ra.s * 8, ra.ph); }
    }
  }
  wg_wait<0>();
  DBG(if (dbgk >= 0 && (threadIdx.x & 127) == 0) { long long* d = g_dbg + (blockIdx.x * 16 + dbgk * 2 + wg) * 4; d[0] = clock64() - cs0; d[1] = wf; d[2] = 0; d[3] = 0; })
#pragma unroll
  for (int m = 0; m < MT; m++) fence_regs(acc[m]);
  if (lane == 0) { mbar_arrive(relA); mbar_arrive(relB); }
}
__device__ __forceinline__ void acquire_stage(uint32_t bars, const Ring& rb, uint32_t s) { mbar_wait(bars + BAR_EB + s * 8, s >= rb.s ? rb.ph ^ 1 : rb.ph); }

template <bool BIAS, bool FINAL>
__device__ __forceinline__ void epi_resid(const float (&acc)[40], uint32_t (&res)[20], const uint32_t (&bias)[10], bf16* out, float2* st,
                                          uint8_t* stage, int row0, int j, int lane) {
  const int q = lane & 3;
  uint32_t* o0 = FINAL ? (uint32_t*)(stage + (row0 & 63) * 160) + q : (uint32_t*)out + lane;
  float s0 = 0.f, t0 = 0.f, s1 = 0.f, t1 = 0.f;
#pragma unroll
  for (int b = 0; b < 10; b++) {
    const float bl = BIAS ? bf_lo(bias[b]) : 0.f, bh = BIAS ? bf_hi(bias[b]) : 0.f;
    const uint32_t p0 = pack_bf16(acc[4 * b] + bl + bf_lo(res[2 * b]), acc[4 * b + 1] + bh + bf_hi(res[2 * b]));
    const uint32_t p1 = pack_bf16(acc[4 * b + 2] + bl + bf_lo(res[2 * b + 1]), acc[4 * b + 3] + bh + bf_hi(res[2 * b + 1]));
    res[2 * b] = p0; res[2 * b + 1] = p1;
    if (FINAL) { o0[b * 4] = p0; o0[b * 4 + 320] = p1; }
    else {
      const int ln = x_line(row0, j * 10 + b);
      o0[ln * 32] = p0; o0[ln * 32 + 256] = p1;
      const float a = bf_lo(p0), c = bf_hi(p0), d = bf_lo(p1), e = bf_hi(p1);
      s0 += a + c; t0 = fmaf(a, a, fmaf(c, c, t0));
      s1 += d + e; t1 = fmaf(d, d, fmaf(e, e, t1));
    }
  }
  if (!FINAL) {
#pragma unroll
    for (int m = 1; m < 4; m <<= 1) {
      s0 += __shfl_xor_sync(0xffffffffu, s0, m); t0 += __shfl_xor_sync(0xffffffffu, t0, m);
      s1 += __shfl_xor_sync(0xffffffffu, s1, m); t1 += __shfl_xor_sync(0xffffffffu, t1, m);
    }
    if (q < 2) st[j * SEQ + row0 + q * 8] = q ? make_float2(s1, t1) : make_float2(s0, t0);
  }
}
__device__ __forceinline__ void publish(unsigned int* f, int wg, int tid) {
  named_bar(2 + wg, 128);
  if ((tid & 127) == 0) flag_signal(f);
}
__device__ __forceinline__ float gelu_half(float s) {
  const float z = s * fmaf(s * s, 8.f * 0.044715f * 0.7978845608028654f, 2.f * 0.7978845608028654f);
  float th;
  asm("tanh.approx.f32 %0, %1;" : "=f"(th) : "f"(z));
  return fmaf(s, th, s);
}
template <bool DOUBLE> __device__ __forceinline__ float2 row_coef(float s, float t) {
  const float mean = s * (1.f / DM);
  const float var = fmaxf(fmaf(-mean, mean, t * (1.f / DM)), 0.f);
  float r = rsqrtf(var + LN_EPS);
  if (DOUBLE) r *= 0.5f * rsqrtf(var * r * r + LN_EPS);
  return make_float2(r, -r * mean);
}
template <bool DOUBLE, int NP> __device__ __forceinline__ void reduce_stats(const float2* st, float2* dst, int i, int lane) {
  float4 v[2][NP];
#pragma unroll
  for (int rr = 0; rr < 2; rr++)
#pragma unroll
    for (int k = 0; k < NP; k++) v[rr][k] = __ldcg((const float4*)(st + k * SEQ + i * 128 + rr * 64) + lane);
#pragma unroll
  for (int rr = 0; rr < 2; rr++) {
    float s0 = 0.f, t0 = 0.f, s1 = 0.f, t1 = 0.f;
#pragma unroll
    for (int k = 0; k < NP; k++) { s0 += v[rr][k].x; t0 += v[rr][k].y; s1 += v[rr][k].z; t1 += v[rr][k].w; }
    dst[rr * 64 + lane * 2] = row_coef<DOUBLE>(s0, t0);
    dst[rr * 64 + lane * 2 + 1] = row_coef<DOUBLE>(s1, t1);
  }
}

template <int PH, bool FIRST, bool LAST>
__global__ void __launch_bounds__(CHAIN_THREADS, 1) chain_kernel(const __grid_constant__ ChainParams p) {
  extern __shared__ __align__(1024) uint8_t smem[];
  const uint32_t sbase = smem_u32(smem), bars = sbase + SM_BAR;
  float* cs = (float*)(smem + SM_CS);
  uint32_t* sb1 = (uint32_t*)(smem + SM_B1);
  const int tid = threadIdx.x, lane = tid & 31, warp = __shfl_sync(0xffffffffu, tid >> 5, 0);
  if (tid == 32) {
    unsigned int* claim = p.flags + 64;
    uint32_t smid;
    asm volatile("mov.u32 %0, %%smid;" : "=r"(smid));
    int t = smid < 160 ? p.pref[smid] : -1;
    if (t >= 0 && atomicExch(claim + t, 1u) != 0u) t = -2;
    if (t == -1) {
#pragma unroll 1
      for (int it = 0; it < 100000; it++) {
        if (*(volatile unsigned int*)(claim + 128) >= 128u) break;
        __nanosleep(200);
      }
    }
    if (t < 0) {
      t = -1;
      if (*(volatile unsigned int*)(claim + 128) < 128u) {
#pragma unroll 1
        for (int c = 0; c < 128 && t < 0; c++)
          if (atomicExch(claim + c, 1u) == 0u) t = c;
      }
    }
    if (t >= 0) atomicAdd(claim + 128, 1u);
    *(volatile int*)(smem + SM_BAR + BAR_TILE) = t;
  }
  unsigned int* fl = p.flags;
  if (tid == 0) {
    for (int s = 0; s < SA; s++) { mbar_init(bars + BAR_FA + s * 8, 1); mbar_init(bars + BAR_EA + s * 8, 4); }
    for (int s = 0; s < SB; s++) { mbar_init(bars + BAR_FB + s * 8, 1); mbar_init(bars + BAR_EB + s * 8, 8); }
    mbar_init(bars + BAR_AUX, 32); mbar_init(bars + BAR_AUX + 8, 32);
    mbar_init(bars + BAR_AUX + 16, FIRST ? 37 : 32); mbar_init(bars + BAR_AUX + 24, 32);
    for (int s = 0; s < 5; s++) { mbar_init(bars + BAR_FH + s * 8, 1); mbar_init(bars + BAR_EH + s * 8, 4); }
    asm volatile("fence.mbarrier_init.release.cluster;" ::: "memory");
  }
  if (tid == 256) {
    if (FIRST) {
      prefetch_map(&p.a_x); prefetch_map(&p.b_wqkv); prefetch_map(&p.b_w1);
    }
    if (LAST) prefetch_map(&p.o_out);
  }
  __syncthreads();
  pdl_launch();
  const int tile = *(volatile int*)(smem + SM_BAR + BAR_TILE);
  if (tile < 0) return;
  const int g = tile >> 4, c = tile & 15;
  if (tid == 0) TS(p.kid, 0);

  if (warp == 9) {
    if (lane == 0) {
      if (FIRST) {
#pragma unroll 1
        for (int kt = 0; kt < 10; kt++) {
          if (kt >= KLIM) mbar_wait(bars + BAR_FB + (kt - KLIM) * 8, 0);
          mbar_expect_tx(bars + BAR_FB + kt * 8, STAGE);
          tma_3d(sbase + SM_B + kt * STAGE, &p.b_wqkv, 0, c, kt * 64, bars + BAR_FB + kt * 8);
          tma_3d(sbase + SM_B + kt * STAGE + 8192, &p.b_wqkv, 64, c, kt * 64, bars + BAR_FB + kt * 8);
        }
#pragma unroll 1
        for (int kt = g; kt < 10; kt += 8) {
          mbar_wait(bars + BAR_FB + kt * 8, 0);
          bulk_s2g(g_wt + WT_QKV + (c * 10 + kt) * STAGE, sbase + SM_B + kt * STAGE, STAGE);
        }
        asm volatile("cp.async.bulk.wait_group.read 0;" ::: "memory");
        mbar_arrive(bars + BAR_AUX + 16);
        asm volatile("cp.async.bulk.wait_group 0;" ::: "memory");
      } else {
        Ring r{0, 0};
        produce_first<10240>(g_wt + WT_WO + (c >> 1) * 10 * 10240, sbase + SM_B, bars + BAR_FB, bars + BAR_EB, r);
        produce<10, 14336, SB, STAGE, BL1>(g_wt + WT_W1 + c * 10 * 14336, sbase + SM_B, bars + BAR_FB, bars + BAR_EB, r);
        pdl_wait();
        produce<18, 15360, SB, STAGE, BL2>(g_wt + WT_W2 + (c >> 1) * 18 * 15360, sbase + SM_B, bars + BAR_FB, bars + BAR_EB, r);
        if (PH & PH_QKV) produce<10, STAGE, SB, STAGE, BL3>(g_wt + WT_QKV + c * 10 * STAGE, sbase + SM_B, bars + BAR_FB, bars + BAR_EB, r);
      }
    }
  } else if (warp == 8) {
    if (lane == 0) {
      Ring r{0, 0};
      if (FIRST) {
#pragma unroll 1
        for (int t = 0; t < 20; t++) {
          mbar_wait(bars + BAR_EA + r.s * 8, r.ph ^ 1);
          mbar_expect_tx(bars + BAR_FA + r.s * 8, STAGE);
          tma_2d(sbase + r.s * STAGE, &p.a_x, (t % 10) * 64, g * 256 + (t / 10) * 128, bars + BAR_FA + r.s * 8);
          ring_adv<SA>(r);
        }
#pragma unroll 1
        for (int job = tile; job < 240; job += 128) {
          const int n = job >> 7;
          mbar_wait(bars + BAR_EB + (3 + n) * 8, 0);
          mbar_expect_tx(bars + BAR_JOB + n * 8, job < 160 ? 14336 : 10240);
#pragma unroll 1
          for (int b = 0; b < (job < 160 ? 7 : 5); b++)
            tma_3d(sbase + SM_B + (3 + n) * STAGE + b * 2048, job < 160 ? &p.b_w1 : &p.b_wo, (job < 160 ? ((job / 10) & 1) * 112 : 0) + b * 16,
                   job < 160 ? job / 20 : job / 10 - 16, (job % 10) * 64, bars + BAR_JOB + n * 8);
        }
#pragma unroll 1
        for (int job = tile; job < 240; job += 128) {
          mbar_wait(bars + BAR_JOB + (job >> 7) * 8, 0);
          bulk_s2g(g_wt + (job < 160 ? WT_W1 + job * 14336 : WT_WO + (job - 160) * 10240), sbase + SM_B + (3 + (job >> 7)) * STAGE, job < 160 ? 14336 : 10240);
        }
        asm volatile("cp.async.bulk.wait_group 0;" ::: "memory");
      } else {
#pragma unroll 1
        for (int s = 0; s < 2; s++) {
          if (s == 0) { pdl_wait(); TS(p.kid, 16); }
          produce<5, 16384, SA>((const uint8_t*)g_o + (g * 4 + s * 2 + (c & 1)) * 10 * 8192, sbase, bars + BAR_FA, bars + BAR_EA, r);
        }
#pragma unroll 1
        for (int s = 0; s < 2; s++) {
          flag_wait(fl + g * 2 + s, 16); fence_async_global(); TS(p.kid, 17 + s * 3);
          produce<10, 16384, SA>((const uint8_t*)g_x1 + (g * 2 + s) * 10 * 16384, sbase, bars + BAR_FA, bars + BAR_EA, r);
        }
        Ring rh{0, 0};
#pragma unroll 1
        for (int s = 0; s < SA; s++) mbar_wait(bars + BAR_EA + s * 8, s >= r.s ? r.ph ^ 1 : r.ph);
        const uint8_t* hsrc = (const uint8_t*)g_h + (g * 4 + (c & 1)) * 18 * 12288;
#pragma unroll 1
        for (int s = 0; s < 2; s++) {
          flag_wait(fl + 16 + g * 2 + s, 16); fence_async_global(); TS(p.kid, 18 + s * 3);
          produce<10, 12288, 5, 12288>(hsrc + s * 36 * 12288, sbase, bars + BAR_FH, bars + BAR_EH, rh);
        }
#pragma unroll 1
        for (int s = 0; s < 2; s++) produce<8, 12288, 5, 12288>(hsrc + (s * 36 + 10) * 12288, sbase, bars + BAR_FH, bars + BAR_EH, rh);
        if (PH & PH_QKV) {
#pragma unroll 1
          for (int s = 0; s < 5; s++) mbar_wait(bars + BAR_EH + s * 8, s >= rh.s ? rh.ph ^ 1 : rh.ph);
        }
        if (PH & PH_QKV) {
#pragma unroll 1
          for (int s = 0; s < 2; s++) {
            flag_wait(fl + 32 + g * 2 + s, 16); fence_async_global(); TS(p.kid, 19 + s * 3);
            produce<10, 16384, SA>((const uint8_t*)g_x2 + (g * 2 + s) * 10 * 16384, sbase, bars + BAR_FA, bars + BAR_EA, r);
          }
        }
      }
    }
  } else if (warp == 10) {
    float2* srow = (float2*)(smem + SM_ROW);
    if (FIRST) {
      named_bar(4, 160);
      if (lane == 0) flag_signal(fl + g * 2 + (c >> 3));
#pragma unroll 1
      for (int s = 0; s < 2; s++) {
        if (lane == 0) flag_wait(fl + g * 2 + s, 8);
        __syncwarp();
        reduce_stats<false, 2>(g_s.st0, srow + s * 128, g * 2 + s, lane);
        mbar_arrive(bars + BAR_AUX + 16 + s * 8);
      }
#pragma unroll 1
      for (int n = 0; n < 2; n++) {
        const int job = n * 128 + tile;
        if (job < 160) {
          mbar_wait(bars + BAR_JOB + n * 8, 0);
          const uint8_t* base = smem + SM_B + (3 + n) * STAGE + ((lane & 15) >> 1) * 2048 + (lane >> 4) * 1024;
          float a[8];
#pragma unroll
          for (int e = 0; e < 8; e++) a[e] = 0.f;
#pragma unroll 4
          for (int r = 0; r < 32; r++) {
            const uint4 v = *(const uint4*)(base + r * 32 + (((lane & 1) ^ ((r >> 2) & 1)) * 16));
            a[0] += bf_lo(v.x); a[1] += bf_hi(v.x); a[2] += bf_lo(v.y); a[3] += bf_hi(v.y);
            a[4] += bf_lo(v.z); a[5] += bf_hi(v.z); a[6] += bf_lo(v.w); a[7] += bf_hi(v.w);
          }
#pragma unroll
          for (int e = 0; e < 8; e++) a[e] += __shfl_xor_sync(0xffffffffu, a[e], 16);
          if (lane < 14) {
            float4* d = (float4*)(g_s.csp_w1 + (job % 10) * 1792 + (job / 10) * 112 + lane * 8);
            d[0] = make_float4(a[0], a[1], a[2], a[3]); d[1] = make_float4(a[4], a[5], a[6], a[7]);
          }
        }
      }
    } else {
      if (lane < 28) {
        float4 v[10], a = make_float4(0.f, 0.f, 0.f, 0.f);
#pragma unroll
        for (int k = 0; k < 10; k++) v[k] = __ldcg((const float4*)(g_s.csp_w1 + k * 1792 + c * 112) + lane);
#pragma unroll
        for (int k = 0; k < 10; k++) { a.x += v[k].x; a.y += v[k].y; a.z += v[k].z; a.w += v[k].w; }
        ((float4*)cs)[lane] = a;
      }
      for (int k = lane; k < 56; k += 32) {
        const int col = (c >> 1) * 216 + (c & 1) * 112 + k * 2;
        const uint32_t v = col < FF ? __ldg((const uint32_t*)(p.b1 + col)) : 0u;
        sb1[k] = pack_bf16(0.5f * bf_lo(v), 0.5f * bf_hi(v));
      }
#pragma unroll 1
      for (int s = 0; s < 2; s++) {
        if (lane == 0) flag_wait(fl + g * 2 + s, 16);
        __syncwarp();
        reduce_stats<true, 8>(g_s.st1, srow + s * 128, g * 2 + s, lane);
        mbar_arrive(bars + BAR_AUX + s * 8);
      }
      if (PH & PH_QKV) {
        const float4 cq = lane < 30 ? __ldcg((const float4*)(g_s.cs_qkv + c * 120) + lane) : make_float4(0.f, 0.f, 0.f, 0.f);
#pragma unroll 1
        for (int s = 0; s < 2; s++) {
          if (lane == 0) { if (s == 0) flag_wait(fl + 16 + g * 2 + 1, 16); flag_wait(fl + 32 + g * 2 + s, 16); }
          __syncwarp();
          if (s == 0 && lane < 30) ((float4*)cs)[lane] = cq;
          reduce_stats<false, 8>(g_s.st2, srow + s * 128, g * 2 + s, lane);
          mbar_arrive(bars + BAR_AUX + 16 + s * 8);
        }
      }
    }
  } else {
    const int wg = warp >> 2, w4 = warp & 3, q = lane & 3;
    const int rbk = g * 2 + wg, rl = w4 * 16 + (lane >> 2);
    const int rowS = rbk * 128 + (c & 1) * 64 + rl, jS = c >> 1;
    const float2* srow = (const float2*)(smem + SM_ROW) + wg * 128;
    const bool t0 = (tid & 127) == 0;
    Ring rb{0, 0};
    uint32_t res[20], bias2[10];
    if (FIRST) {
      if (wg == 1) {
        const int xrow = g * 256 + c * 16 + (w4 & 1) * 8 + (lane >> 2), xcg = (w4 >> 1) * 40 + q;
        uint4 xv[10];
#pragma unroll
        for (int k = 0; k < 10; k++) xv[k] = __ldg((const uint4*)(p.xin + (size_t)xrow * DM) + xcg + k * 4);
        float xs = 0.f, xt = 0.f;
#pragma unroll
        for (int k = 0; k < 10; k++) {
          const uint32_t e[4] = {xv[k].x, xv[k].y, xv[k].z, xv[k].w};
#pragma unroll
          for (int m = 0; m < 4; m++) { const float a = bf_lo(e[m]), b = bf_hi(e[m]); xs += a + b; xt = fmaf(a, a, fmaf(b, b, xt)); }
        }
#pragma unroll
        for (int m = 1; m < 4; m <<= 1) { xs += __shfl_xor_sync(0xffffffffu, xs, m); xt += __shfl_xor_sync(0xffffffffu, xt, m); }
        if (q == 0) g_s.st0[(w4 >> 1) * SEQ + xrow] = make_float2(xs, xt);
        asm volatile("bar.arrive 4, 160;" ::: "memory");
#pragma unroll
        for (int k = 0; k < 10; k++) *((uint4*)g_x0 + x_line(xrow, xcg + k * 4) * 8 + (xrow & 7)) = xv[k];
        float o[60];
        const uint32_t one = 0x3F803F80u;
#pragma unroll 1
        for (int kt = 0; kt < 10; kt++) {
          mbar_wait(bars + BAR_FB + kt * 8, 0);
          wg_fence();
#pragma unroll
          for (int k = 0; k < 4; k++) wgmma_rs_n120<1>(o, one, one, one, one, b_desc<64, true>(sbase + SM_B + kt * STAGE) + k * 128, (kt | k) != 0);
          wg_commit();
        }
        wg_wait<0>();
        fence_regs(o);
        if ((tid & 127) < 4) {
#pragma unroll
          for (int b = 0; b < 15; b++) {
            *(float2*)(cs + b * 8 + q * 2) = make_float2(o[4 * b], o[4 * b + 1]);
            if (g == 0) *(float2*)(g_s.cs_qkv + c * 120 + b * 8 + q * 2) = make_float2(o[4 * b], o[4 * b + 1]);
          }
          mbar_arrive(bars + BAR_AUX + 16);
        }
        named_bar(3, 128);
      }
    } else {
#pragma unroll
      for (int b = 0; b < 10; b++) {
        const uint32_t* r0 = (const uint32_t*)p.xres + x_line(rowS, jS * 10 + b) * 32 + lane;
        res[2 * b] = __ldcg(r0); res[2 * b + 1] = __ldcg(r0 + 256);
      }
      {
        float acc[1][40];
        if (t0) TS(p.kid, 1 + wg * 24);
        mainloop<80, 1, 10, 64, 2, true, false>(acc, sbase, bars, lane, wg, wg * 5, wg != 0, rb, 0, p.kid == 2 ? 0 : -1);
        if (t0) TS(p.kid, 2 + wg * 24);
        epi_resid<false, false>(acc[0], res, bias2, g_x1, g_s.st1, smem, rowS, jS, lane);
        if (wg == 0) asm volatile("bar.arrive 5, 256;" ::: "memory");
        publish(fl + rbk, wg, tid);
      }
      {
        float acc[2][56];
        if (t0) TS(p.kid, 3 + wg * 24);
        mainloop<112, 2, 10, 64, 1, true, false>(acc, sbase, bars, lane, wg, 10 + wg * 10, true, rb, 0, p.kid == 2 ? 1 : -1);
        if (t0) TS(p.kid, 4 + wg * 24);
        mbar_wait(bars + BAR_AUX + wg * 8, 0);
        const float2 c0 = srow[rl], c1 = srow[rl + 8], c2 = srow[rl + 64], c3 = srow[rl + 72];
        const int cg0 = (c >> 1) * 27 + (c & 1) * 14;
        uint32_t* o0 = (uint32_t*)g_h + h_line(rbk * 128 + rl, cg0) * 32 + lane;
        int kg = cg0 % 12;
#pragma unroll
        for (int b = 0; b < 14; b++) {
          if (b < 13 || !(c & 1)) {
            const float2 cc = *(const float2*)(cs + b * 8 + q * 2);
            const uint32_t bb = sb1[b * 4 + q];
            const float bl = bf_lo(bb), bh = bf_hi(bb);
            o0[0] = pack_bf16(gelu_half(fmaf(c0.x, acc[0][4 * b], fmaf(c0.y, cc.x, bl))), gelu_half(fmaf(c0.x, acc[0][4 * b + 1], fmaf(c0.y, cc.y, bh))));
            o0[384] = pack_bf16(gelu_half(fmaf(c1.x, acc[0][4 * b + 2], fmaf(c1.y, cc.x, bl))), gelu_half(fmaf(c1.x, acc[0][4 * b + 3], fmaf(c1.y, cc.y, bh))));
            o0[18 * 3072] = pack_bf16(gelu_half(fmaf(c2.x, acc[1][4 * b], fmaf(c2.y, cc.x, bl))), gelu_half(fmaf(c2.x, acc[1][4 * b + 1], fmaf(c2.y, cc.y, bh))));
            o0[18 * 3072 + 384] = pack_bf16(gelu_half(fmaf(c3.x, acc[1][4 * b + 2], fmaf(c3.y, cc.x, bl))), gelu_half(fmaf(c3.x, acc[1][4 * b + 3], fmaf(c3.y, cc.y, bh))));
            o0 += (++kg == 12) ? (96 - 11) * 32 : 32;
            if (kg == 12) kg = 0;
          }
        }
        if (t0) TS(p.kid, 5 + wg * 24);
        publish(fl + 16 + rbk, wg, tid);
      }
      {
#pragma unroll
        for (int b = 0; b < 10; b++) bias2[b] = __ldg((const uint32_t*)(p.b2 + jS * 80) + b * 4 + q);
        float acc[1][40];
        mainloop<80, 1, 10, 96, 1, true, false, true>(acc, sbase, bars, lane, wg, wg * 10, true, rb, 0, p.kid == 2 ? 2 : -1);
        mainloop<80, 1, 8, 96, 1, true, false, true>(acc, sbase, bars, lane, wg, 20 + wg * 8, LAST ? wg == 0 : wg != 0, rb, 1, p.kid == 2 ? 3 : -1);
        if (t0) TS(p.kid, 6 + wg * 24);
        if (LAST) {
          const uint32_t st = (rb.s + wg) % SB;
          acquire_stage(bars, rb, st);
          epi_resid<true, true>(acc[0], res, bias2, nullptr, nullptr, smem + SM_B + st * STAGE, rowS, jS, lane);
          asm volatile("fence.proxy.async.shared::cta;" ::: "memory");
          named_bar(2 + wg, 128);
          if (t0) {
            asm volatile("cp.async.bulk.tensor.2d.global.shared::cta.bulk_group [%0, {%2, %3}], [%1];" ::"l"(&p.o_out), "r"(sbase + SM_B + st * STAGE), "r"(jS * 80),
                         "r"(rbk * 128 + (c & 1) * 64) : "memory");
            asm volatile("cp.async.bulk.commit_group;\ncp.async.bulk.wait_group 0;" ::: "memory");
          }
        } else {
          epi_resid<true, false>(acc[0], res, bias2, g_x2, g_s.st2, smem, rowS, jS, lane);
          if (wg == 0) asm volatile("bar.arrive 5, 256;" ::: "memory");
          publish(fl + 32 + rbk, wg, tid);
        }
      }
    }
    if (PH & PH_QKV) {
      float acc[2][60];
      if (t0) TS(p.kid, 10 + wg * 2);
      mainloop<120, 2, 10, 64, 1, !FIRST, true>(acc, sbase, bars, lane, wg, (FIRST ? 0 : 30) + wg * 10, wg == 0, rb, 0, p.kid == 2 ? 4 : 5);
      if (t0) TS(p.kid, 11 + wg * 2);
      mbar_wait(bars + BAR_AUX + 16 + wg * 8, 0);
      pdl_wait();
      const float QS = 0.22360679774997896f * 1.4426950408889634f;
      unsigned int* smax = sb1 + 16 + wg * 8;
      if ((tid & 127) < 6) smax[tid & 127] = 0u;
      named_bar(2 + wg, 128);
      int off[5];
#pragma unroll
      for (int m = 0; m < 5; m++) {
        const int cc = m * 8 + q * 2, hh = cc >= 20, d = cc - hh * 20;
        off[m] = hh * 6144 + (d >> 3) * 128 + (d & 7) * 2;
      }
#pragma unroll
      for (int pr = 0; pr < 3; pr++) {
        const int part = (c * 6 + pr * 2) >> 5;
        float nrm[2];
        const uint32_t sst = (rb.s + pr) % SB, soff = wg ? pr * STAGE : SM_B + sst * STAGE;
        if (wg == 0) acquire_stage(bars, rb, sst);
        uint8_t* stg = smem + soff + w4 * 768 + (lane >> 2) * 16;
#pragma unroll
        for (int mt = 0; mt < 2; mt++) {
          const float2 c0 = srow[mt * 64 + rl], c1 = srow[mt * 64 + rl + 8];
          const bool mu0 = is_mufu(mt * 8 + w4 * 2), mu1 = is_mufu(mt * 8 + w4 * 2 + 1), mu = (q & 1) ? mu1 : mu0;
          const float s0 = part == 0 ? QS : (part == 1 && !mu0 ? 0x1p-22f : 1.f), s1 = part == 0 ? QS : (part == 1 && !mu1 ? 0x1p-22f : 1.f);
          const float a0 = c0.x * s0, b0 = c0.y * s0, a1 = c1.x * s1, b1 = c1.y * s1;
          float nA0 = 0.f, nA1 = 0.f, nB0 = 0.f, nB1 = 0.f;
#pragma unroll
          for (int m = 0; m < 5; m++) {
            const int b = pr * 5 + m;
            const float2 cc = *(const float2*)(cs + b * 8 + q * 2);
            uint8_t* ptr = stg + off[m] + mt * 3072;
            const float v0 = fmaf(a0, acc[mt][4 * b], b0 * cc.x), v1 = fmaf(a0, acc[mt][4 * b + 1], b0 * cc.y);
            const float v2 = fmaf(a1, acc[mt][4 * b + 2], b1 * cc.x), v3 = fmaf(a1, acc[mt][4 * b + 3], b1 * cc.y);
            *(uint32_t*)ptr = pack_bf16(v0, v1);
            *(uint32_t*)(ptr + 384) = pack_bf16(v2, v3);
            const float n0 = fmaf(v0, v0, v1 * v1), n1 = fmaf(v2, v2, v3 * v3);
            if (m < 2) { nA0 += n0; nA1 += n1; } else if (m > 2) { nB0 += n0; nB1 += n1; }
            else if (q < 2) { nA0 += n0; nA1 += n1; } else { nB0 += n0; nB1 += n1; }
          }
          const uint2 ex = part == 0 ? make_uint2(0x3F803F80u, 0x00003F80u)
                                     : (part == 1 ? (mu ? make_uint2(0u, 0u) : make_uint2(0x377C3C00u, 0x00003020u)) : make_uint2(0x00003F80u, 0u));
          *(uint2*)(stg + mt * 3072 + (q >> 1) * 6144 + (q & 1) * 384 + 264) = ex;
          float x = (q & 1) ? nA1 : nA0, y = (q & 1) ? nB1 : nB0;
          x += __shfl_xor_sync(0xffffffffu, (q & 1) ? nA0 : nA1, 1);
          y += __shfl_xor_sync(0xffffffffu, (q & 1) ? nB0 : nB1, 1);
          float n = (q & 2) ? y : x;
          n += __shfl_xor_sync(0xffffffffu, (q & 2) ? x : y, 2);
          nrm[mt] = (part == 1 && !mu) ? n * 0x1p44f : n;
        }
        asm volatile("fence.proxy.async.shared::cta;" ::: "memory");
        named_bar(2 + wg, 128);
        if ((tid & 127) < 2) bulk_s2g((uint8_t*)g_qkv + (size_t)(c * 6 + pr * 2 + lane) * HEAD_BYTES + rbk * 6144, sbase + soff + lane * 6144, 6144);
        if (part < 2) atomicMax(smax + pr * 2 + (q >> 1), max(__float_as_uint(nrm[0]) & 0x7FFFFFFFu, __float_as_uint(nrm[1]) & 0x7FFFFFFFu));
      }
      named_bar(2 + wg, 128);
      if ((tid & 127) < 6 && c * 6 + (tid & 127) < 64) atomicMax(fl + NORM_OFF + c * 6 + (tid & 127), smax[tid & 127]);
      if ((tid & 127) < 2) {
        asm volatile("cp.async.bulk.wait_group 0;" ::: "memory");
      }
    }
    if (t0) TS(p.kid, 14 + wg);
  }
}

__device__ __forceinline__ uint32_t exp2_poly_pair(float a0, float a1) {
  const uint32_t v = __byte_perm(__float_as_uint(a0), __float_as_uint(a1), 0x7430);
  const uint32_t e = __byte_perm(__float_as_uint(a0), __float_as_uint(a1), 0x6521);
  uint32_t u;
  asm("fma.rn.f16x2 %0, %1, %2, %3;" : "=r"(u) : "r"(v), "r"(0x1d611d61u), "r"(0xa012a012u));
  asm("fma.rn.f16x2 %0, %1, %2, %3;" : "=r"(u) : "r"(u), "r"(v), "r"(0x21622162u));
  uint32_t r;
  asm("{\n.reg .b32 t;\nshl.b32 t, %1, 7;\nadd.u32 %0, t, %2;\n}" : "=r"(r) : "r"(e), "r"(u));
  return r;
}
constexpr int KPITCH = 6144 + 128;
constexpr int ATT_V = 16 * KPITCH, ATT_JOB = ATT_V + HEAD_BYTES, ATT_BAR = ATT_JOB + 2 * 15360, ATT_SMEM = ATT_BAR + 128;

__device__ __forceinline__ void att_store(const float (&O)[12], int row0, int h, int lane) {
  const float l0 = __shfl_sync(0xffffffffu, O[8], (lane & ~3) | 2), l1 = __shfl_sync(0xffffffffu, O[10], (lane & ~3) | 2);
  const float r0 = __fdividef(1.f, l0), r1 = __fdividef(1.f, l1);
#pragma unroll
  for (int c = 0; c < 3; c++)
    if (c < 2 || (lane & 3) < 2) {
      const int col = h * 20 + c * 8 + (lane & 3) * 2;
      uint32_t* o0 = (uint32_t*)g_o + o_line(row0, col >> 3) * 32 + (row0 & 7) * 4 + ((col & 7) >> 1);
      o0[0] = pack_bf16(O[4 * c] * r0, O[4 * c + 1] * r0);
      o0[256] = pack_bf16(O[4 * c + 2] * r1, O[4 * c + 3] * r1);
    }
}

struct alignas(64) AttParams {
  CUtensorMap b_w2;
  const unsigned int* norms;
  unsigned int *reset_a, *reset_b, *reset_c;
  const uint32_t* zeros;
  int kid, jobs;
};
__global__ void __launch_bounds__(512, 1) att_kernel(const __grid_constant__ AttParams p) {
  const unsigned int* norms = p.norms;
  extern __shared__ __align__(1024) uint8_t smem[];
  const uint32_t sK = smem_u32(smem), sV = sK + ATT_V, bars = sK + ATT_BAR;
  const int h = blockIdx.x >> 2, qt = blockIdx.x & 3;
  const int tid = threadIdx.x, lane = tid & 31, wg = __shfl_sync(0xffffffffu, tid >> 7, 0), warp = (tid >> 5) & 3;
  if (tid == 0) {
    for (int c = 0; c < 9; c++) mbar_init(bars + c * 8, 1);
    asm volatile("fence.mbarrier_init.release.cluster;" ::: "memory");
  }
  *(uint32_t*)(smem + (tid >> 5) * KPITCH + 6144 + lane * 4) = 0u;
  asm volatile("fence.proxy.async;" ::: "memory");
  const uint32_t z0 = __ldg(p.zeros + (tid & 1)), z1 = __ldg(p.zeros + 2 + (tid & 1));
  __syncthreads();
  pdl_wait();
  pdl_launch();
  if (tid == 0) TS(p.kid, 1);
  const uint8_t* gq = (const uint8_t*)g_qkv + (size_t)h * HEAD_BYTES;
  const uint64_t dK = mk_desc(sK, 128, 384, 0);
  const uint64_t dV = mk_desc(sV, 384, 128, 0);
  uint32_t q[6];
  auto load_q = [&](int row0) {
    const uint32_t* qa = (const uint32_t*)(gq + (row0 >> 3) * 384 + (row0 & 7) * 16) + (lane & 3);
    q[0] = __ldcg(qa); q[1] = __ldcg(qa + 96); q[2] = __ldcg(qa + 32); q[3] = __ldcg(qa + 128); q[4] = __ldcg(qa + 64); q[5] = __ldcg(qa + 160);
  };
  const int rowA = qt * 512 + wg * 64 + warp * 16 + (lane >> 2);
  load_q(rowA);
  auto load_kv = [&](int c) {
    mbar_expect_tx(bars + c * 8, 24576);
    bulk_g2s(sK + c * 2 * KPITCH, gq + 32 * HEAD_BYTES + c * 12288, 6144, bars + c * 8);
    bulk_g2s(sK + (c * 2 + 1) * KPITCH, gq + 32 * HEAD_BYTES + c * 12288 + 6144, 6144, bars + c * 8);
    bulk_g2s(sV + c * 12288, gq + 64 * HEAD_BYTES + c * 12288, 12288, bars + c * 8);
  };
  if (tid == 480) { load_kv(0); load_kv(1); }
  __syncwarp();
  auto load_rest = [&]() {
        if (tid == 480) {
#pragma unroll 1
          for (int c = 2; c < 8; c++) load_kv(c);
          if (p.jobs) {
            mbar_expect_tx(bars + 64, blockIdx.x < 16 ? 30720 : 15360);
#pragma unroll 1
            for (int job = blockIdx.x; job < 144; job += 128)
#pragma unroll 1
              for (int b = 0; b < 5; b++) tma_3d(sK + ATT_JOB + (job >> 7) * 15360 + b * 3072, &p.b_w2, b * 16, job / 18, (job % 18) * 96, bars + 64);
          }
        }
        __syncwarp();
  };
  const bool unsafe = !(__uint_as_float(__ldcg(norms + h)) * __uint_as_float(__ldcg(norms + 32 + h)) <= 3500.f);
  if (blockIdx.x == 0 && tid < NORM_OFF) { p.reset_a[tid] = 0u; if (tid < FLAG_SET - NORM_OFF) p.reset_b[tid] = 0u; if (p.reset_c) p.reset_c[tid] = 0u; }
  auto fast_tile = [&](auto first, int row0) -> bool {
      constexpr int tt = first.value ? 0 : 1;
      float S[64], O[12];
      uint32_t P[32];
#pragma unroll
      for (int k = 0; k < 64; k++) S[k] = 0.f;
#pragma unroll
      for (int k = 0; k < 12; k++) O[k] = 0.f;
      auto blocks = [&](int g0, int g1) {
        uint64_t gk = dK + g0 * (KPITCH / 16), gv = dV + g0 * 384;
#pragma unroll 1
        for (int g = g0; g < g1; g++) {
        if (tt == 0 && (g & 1) == 0) mbar_wait_warp(bars + (g >> 1) * 8, 0);
        wg_fence();
        wgmma_rs_n128<0>(S, q[0], q[1], q[2], q[3], gk, 0);
        wgmma_rs_n128<0>(S, q[4], q[5], z0, z1, gk + 16, 1);
        wg_commit();
        wg_wait<0>();
        fence_regs(S);
#pragma unroll
        for (int hf = 0; hf < NSPLIT; hf++) {
          constexpr int NB = 16 / NSPLIT;
          uint32_t (&Ph)[2 * NB] = *(uint32_t(*)[2 * NB])(P + hf * 2 * NB);
#pragma unroll
          for (int b = hf * NB; b < hf * NB + NB; b++) {
            if (is_mufu(b)) { P[2 * b] = pack_bf16(ex2(S[4 * b]), ex2(S[4 * b + 1])); P[2 * b + 1] = pack_bf16(ex2(S[4 * b + 2]), ex2(S[4 * b + 3])); }
            else { P[2 * b] = exp2_poly_pair(S[4 * b], S[4 * b + 1]); P[2 * b + 1] = exp2_poly_pair(S[4 * b + 2], S[4 * b + 3]); }
          }
          fence_regs(Ph);
          wg_fence();
#pragma unroll
          for (int s = hf * NB / 2; s < (hf + 1) * NB / 2; s++) wgmma_rs_n24<1>(O, P[4 * s], P[4 * s + 1], P[4 * s + 2], P[4 * s + 3], gv + s * 48, 1);
          wg_commit();
        }
        wg_wait<0>();
        gk += KPITCH / 16; gv += 384;
        }
      };
      if (tt == 0) {
        blocks(0, 2);
        load_rest();
        blocks(2, 16);
      } else blocks(0, 16);
      fence_regs(O);
      if (tid == 0) TS(p.kid, 2 + tt);
      att_store(O, row0, h, lane);
      bool bad = false;
      float m = 0.f;
#pragma unroll
      for (int k = 0; k < 12; k++) { m = fmaxf(m, fabsf(O[k])); bad |= (O[k] != O[k]); }
      bad |= !(m <= 3e38f);
      if ((lane & 3) == 2) bad |= !(O[8] >= 0x1p-20f) || !(O[10] >= 0x1p-20f);
      uint32_t r;
      asm volatile("{\n.reg .pred p, r;\nsetp.ne.u32 p, %1, 0;\nbarrier.red.or.pred.aligned r, %2, 128, p;\nselp.u32 %0, 1, 0, r;\n}\n" : "=r"(r) : "r"((uint32_t)bad), "r"(1 + wg) : "memory");
      return r != 0;
  };
  auto safe_tile = [&](int row0) {
      float S[64], O[12];
      uint32_t P[32];
#pragma unroll
      for (int k = 0; k < 64; k++) S[k] = 0.f;
      if ((lane & 3) >= 2) { q[4] = 0u; q[5] = 0u; }
      float m0 = -INFINITY, m1 = -INFINITY;
#pragma unroll
      for (int k = 0; k < 12; k++) O[k] = 0.f;
      uint64_t gk = dK, gv = dV;
#pragma unroll 1
      for (int g = 0; g < 16; g++) {
        wg_fence();
        wgmma_rs_n128<0>(S, q[0], q[1], q[2], q[3], gk, 0);
        wgmma_rs_n128<0>(S, q[4], q[5], z0, z1, gk + 16, 1);
        wg_commit();
        wg_wait<0>();
        fence_regs(S);
        float x0 = m0, x1 = m1;
#pragma unroll
        for (int b = 0; b < 16; b++) {
          if (!is_mufu(b)) { S[4 * b] *= 0x1p22f; S[4 * b + 1] *= 0x1p22f; S[4 * b + 2] *= 0x1p22f; S[4 * b + 3] *= 0x1p22f; }
          x0 = fmaxf(x0, fmaxf(S[4 * b], S[4 * b + 1]));
          x1 = fmaxf(x1, fmaxf(S[4 * b + 2], S[4 * b + 3]));
        }
        x0 = fmaxf(x0, __shfl_xor_sync(0xffffffffu, x0, 1)); x1 = fmaxf(x1, __shfl_xor_sync(0xffffffffu, x1, 1));
        x0 = fmaxf(x0, __shfl_xor_sync(0xffffffffu, x0, 2)); x1 = fmaxf(x1, __shfl_xor_sync(0xffffffffu, x1, 2));
        const float al0 = ex2(m0 - x0), al1 = ex2(m1 - x1);
        m0 = x0; m1 = x1;
#pragma unroll
        for (int c = 0; c < 3; c++) { O[4 * c] *= al0; O[4 * c + 1] *= al0; O[4 * c + 2] *= al1; O[4 * c + 3] *= al1; }
#pragma unroll
        for (int b = 0; b < 16; b++) {
          P[2 * b] = pack_bf16(ex2(S[4 * b] - m0), ex2(S[4 * b + 1] - m0));
          P[2 * b + 1] = pack_bf16(ex2(S[4 * b + 2] - m1), ex2(S[4 * b + 3] - m1));
        }
        fence_regs(P);
        fence_regs(O);
        wg_fence();
#pragma unroll
        for (int s = 0; s < 8; s++) wgmma_rs_n24<1>(O, P[4 * s], P[4 * s + 1], P[4 * s + 2], P[4 * s + 3], gv + s * 48, 1);
        wg_commit();
        wg_wait<0>();
        fence_regs(O);
        gk += KPITCH / 16; gv += 384;
      }
      att_store(O, row0, h, lane);
      named_bar(1 + wg, 128);
  };
  bool redo = true;
  if (!__any_sync(0xffffffffu, unsafe)) redo = fast_tile(IC<1>{}, rowA);
  else {
    load_rest();
#pragma unroll 1
    for (int c = 0; c < 8; c++) mbar_wait(bars + c * 8, 0);
  }
  if (__any_sync(0xffffffffu, redo)) safe_tile(rowA);
  load_q(rowA + 256);
  if (tid == 480 && p.jobs) {
    mbar_wait(bars + 64, 0);
#pragma unroll 1
    for (int job = blockIdx.x; job < 144; job += 128) bulk_s2g(g_wt + WT_W2 + job * 15360, sK + ATT_JOB + (job >> 7) * 15360, 15360);
  }
  __syncwarp();
  redo = true;
  if (!__any_sync(0xffffffffu, unsafe)) redo = fast_tile(IC<0>{}, rowA + 256);
  if (__any_sync(0xffffffffu, redo)) safe_tile(rowA + 256);
  if (tid == 480) asm volatile("cp.async.bulk.wait_group 0;" ::: "memory");
  if (tid == 0) TS(p.kid, 4);
}

typedef CUresult (*EncodeFn)(CUtensorMap*, CUtensorMapDataType, cuuint32_t, void*, const cuuint64_t*, const cuuint64_t*, const cuuint32_t*,
                             const cuuint32_t*, CUtensorMapInterleave, CUtensorMapSwizzle, CUtensorMapL2promotion, CUtensorMapFloatOOBfill);

static void make_a(EncodeFn enc, CUtensorMap* m, const void* ptr, int K) {
  cuuint64_t dims[2] = {(cuuint64_t)K, (cuuint64_t)SEQ}, strides[1] = {(cuuint64_t)K * 2};
  cuuint32_t box[2] = {64, 128}, es[2] = {1, 1};
  enc(m, CU_TENSOR_MAP_DATA_TYPE_BFLOAT16, 2, (void*)ptr, dims, strides, box, es, CU_TENSOR_MAP_INTERLEAVE_NONE, CU_TENSOR_MAP_SWIZZLE_128B,
      CU_TENSOR_MAP_L2_PROMOTION_NONE, CU_TENSOR_MAP_FLOAT_OOB_FILL_NONE);
}
static void make_out(EncodeFn enc, CUtensorMap* m, void* ptr) {
  cuuint64_t dims[2] = {(cuuint64_t)DM, (cuuint64_t)SEQ}, strides[1] = {(cuuint64_t)DM * 2};
  cuuint32_t box[2] = {80, 64}, es[2] = {1, 1};
  enc(m, CU_TENSOR_MAP_DATA_TYPE_BFLOAT16, 2, ptr, dims, strides, box, es, CU_TENSOR_MAP_INTERLEAVE_NONE, CU_TENSOR_MAP_SWIZZLE_NONE,
      CU_TENSOR_MAP_L2_PROMOTION_NONE, CU_TENSOR_MAP_FLOAT_OOB_FILL_NONE);
}
static void make_b(EncodeFn enc, CUtensorMap* m, const void* ptr, int K, int N, int BN, int bk, int bw) {
  cuuint64_t dims[3] = {(cuuint64_t)BN, (cuuint64_t)(N / BN), (cuuint64_t)K}, strides[2] = {(cuuint64_t)BN * 2, (cuuint64_t)N * 2};
  cuuint32_t box[3] = {(cuuint32_t)bw, 1, (cuuint32_t)bk}, es[3] = {1, 1, 1};
  enc(m, CU_TENSOR_MAP_DATA_TYPE_BFLOAT16, 3, (void*)ptr, dims, strides, box, es, CU_TENSOR_MAP_INTERLEAVE_NONE, bw == 64 ? CU_TENSOR_MAP_SWIZZLE_128B : CU_TENSOR_MAP_SWIZZLE_32B,
      CU_TENSOR_MAP_L2_PROMOTION_NONE, CU_TENSOR_MAP_FLOAT_OOB_FILL_NONE);
}
template <typename... KArgs, typename... Args>
static void launch(void (*kern)(KArgs...), int grid, int threads, int smem, bool pdl, Args... args) {
  cudaFuncSetAttribute(kern, cudaFuncAttributeMaxDynamicSharedMemorySize, smem);
  cudaLaunchConfig_t cfg = {};
  cfg.gridDim = dim3(grid); cfg.blockDim = dim3(threads); cfg.dynamicSmemBytes = smem; cfg.stream = cudaStreamPerThread;
  cudaLaunchAttribute at[1];
  at[0].id = cudaLaunchAttributeProgrammaticStreamSerialization; at[0].val.programmaticStreamSerializationAllowed = 1;
  cfg.attrs = at; cfg.numAttrs = pdl ? 1 : 0;
  cudaLaunchKernelEx(&cfg, kern, KArgs(args)...);
}

static void make_pref(signed char* pref, int ntpc) {
  auto kern = chain_kernel<PH_WO | PH_W1 | PH_W2, false, true>;
  cudaFuncSetAttribute(kern, cudaFuncAttributeMaxDynamicSharedMemorySize, CHAIN_SMEM);
  cudaFuncSetAttribute(kern, cudaFuncAttributeNonPortableClusterSizeAllowed, 1);
  int n[10] = {0};
  for (int t = 2; t <= 8; t++) {
    cudaLaunchConfig_t cfg = {};
    cfg.gridDim = dim3(2 * t * 16); cfg.blockDim = dim3(CHAIN_THREADS); cfg.dynamicSmemBytes = CHAIN_SMEM;
    cudaLaunchAttribute at[1];
    at[0].id = cudaLaunchAttributeClusterDimension; at[0].val.clusterDim.x = 2 * t; at[0].val.clusterDim.y = 1; at[0].val.clusterDim.z = 1;
    cfg.attrs = at; cfg.numAttrs = 1;
    if (cudaOccupancyMaxActiveClusters(&n[t], kern, &cfg) != cudaSuccess) { n[t] = -1; cudaGetLastError(); }
  }
  int best[10] = {0}, cnt[10], found = 0;
  for (int code = 0; code < 1000000 && !found; code++) {
    int c = code, tot = 0, g = 0;
    for (int m = 0; m < 10; m++) cnt[m] = 0;
    for (int m = 4; m <= 9; m++) { cnt[m] = c % 10; c /= 10; tot += cnt[m] * m; g += cnt[m]; }
    if (g > 9 || tot > ntpc) continue;
    bool ok = true;
    for (int t = 3; t <= 8 && ok; t++) { int s = 0; for (int m = 4; m <= 9; m++) s += cnt[m] * (m / t); ok = (s == n[t]); }
    if (ok) { found = 1; for (int m = 0; m < 10; m++) best[m] = cnt[m]; }
  }
  int grp[80], size[10], ng = 0, id = 0;
  for (int t = 0; t < 80; t++) { grp[t] = -1; pref[2 * t] = pref[2 * t + 1] = -1; }
  if (found) {
    for (int m = 4; m <= 9; m++) for (int k = 0; k < best[m]; k++) size[ng++] = m;
    for (int r = 0; r < 9; r++) for (int g = 0; g < ng; g++) if (size[g] > r && id < ntpc) grp[id++] = g;
  }
  int nb = 0;
  bool used[80] = {false};
  auto put = [&](int t, int blk, int w) {
    const int tile = blk * 16 + w * 2;
    pref[2 * t] = (signed char)tile; pref[2 * t + 1] = (signed char)(tile + 1); used[t] = true;
  };
  for (int g = 0; g < ng && nb < 8; g++)
    if (size[g] >= 8) {
      int w = 0;
      for (int t = 0; t < ntpc && w < 8; t++) if (grp[t] == g) put(t, nb, w++);
      nb++;
    }
  int pos = nb * 8;
  for (int pass = 0; pass < 2; pass++)
    for (int g = 0; g <= ng; g++)
      for (int t = 0; t < ntpc && pos < 64; t++)
        if (!used[t] && (g < ng ? (grp[t] == g && (size[g] < 8) == (pass == 0)) : (pass == 1 && grp[t] < 0))) { put(t, pos >> 3, pos & 7); pos++; }
}

extern "C" void kernel_launch(void* const* d_in, const int* in_sizes, int n_in, void* d_out, int out_size) {
  const bf16* x = (const bf16*)d_in[0];
  const bf16* wqkv = (const bf16*)d_in[1];
  const bf16* wo = (const bf16*)d_in[2];
  const bf16* w1 = (const bf16*)d_in[4];
  const bf16* b1 = (const bf16*)d_in[5];
  const bf16* w2 = (const bf16*)d_in[6];
  const bf16* b2 = (const bf16*)d_in[7];
  void* fn = nullptr;
  cudaDriverEntryPointQueryResult qr;
  cudaGetDriverEntryPoint("cuTensorMapEncodeTiled", &fn, cudaEnableDefault, &qr);
  EncodeFn enc = (EncodeFn)fn;
  void *px0, *px2, *pf, *pz;
  cudaGetSymbolAddress(&px0, g_x0);
  cudaGetSymbolAddress(&px2, g_x2); cudaGetSymbolAddress(&pf, g_s);
  unsigned int* flags = ((Small*)pf)->flags;
  pz = ((Small*)pf)->zeros;

  int nsm = 132;
  cudaDeviceGetAttribute(&nsm, cudaDevAttrMultiProcessorCount, 0);
  const int ngrid = nsm >= 128 ? (nsm > 160 ? 160 : (nsm & ~1)) : 128;
  ChainParams p;
  make_pref(p.pref, ngrid / 2);
  make_a(enc, &p.a_x, x, DM);
  make_out(enc, &p.o_out, d_out);
  AttParams ap;
  make_b(enc, &p.b_wo, wo, DM, DM, 80, 64, 16); make_b(enc, &p.b_w1, w1, DM, FF, 216, 64, 16); make_b(enc, &ap.b_w2, w2, FF, DM, 80, 96, 16);
  ap.zeros = (const uint32_t*)pz;
  make_b(enc, &p.b_wqkv, wqkv, DM, 1920, 120, 64, 64);
  p.xres = (const bf16*)px0; p.xin = x; p.b1 = b1; p.b2 = b2; p.flags = flags; p.kid = 0;

  launch(chain_kernel<PH_QKV, true, false>, ngrid, CHAIN_THREADS, CHAIN_SMEM, false, p);
  ap.norms = flags + NORM_OFF; ap.reset_a = flags; ap.reset_b = flags + FLAG_SET + NORM_OFF; ap.reset_c = flags + 2 * FLAG_SET; ap.kid = 1; ap.jobs = 1;
  launch(att_kernel, 128, 512, ATT_SMEM, true, ap);
  p.flags = flags + FLAG_SET; p.kid = 2;
  launch(chain_kernel<PH_WO | PH_W1 | PH_W2 | PH_QKV, false, false>, ngrid, CHAIN_THREADS, CHAIN_SMEM, true, p);
  ap.norms = flags + FLAG_SET + NORM_OFF; ap.reset_a = flags + FLAG_SET; ap.reset_b = flags + NORM_OFF; ap.reset_c = nullptr; ap.kid = 3; ap.jobs = 0;
  launch(att_kernel, 128, 512, ATT_SMEM, true, ap);
  p.kid = 4; p.xres = (const bf16*)px2; p.flags = flags + 2 * FLAG_SET;
  launch(chain_kernel<PH_WO | PH_W1 | PH_W2, false, true>, ngrid, CHAIN_THREADS, CHAIN_SMEM, true, p);
}
```

```cpp
#include <cuda_runtime.h>
#include <cuda_bf16.h>
#include <cuda.h>
#include <stdint.h>

typedef __nv_bfloat16 bf16;

constexpr int SEQ = 2048, DM = 640, FF = 1728;
constexpr float LN_EPS = 1e-5f;
constexpr int HEAD_BYTES = 98304;
constexpr uint32_t MUFU_MASK = 0x4949u;
__host__ __device__ constexpr bool is_mufu(int g) { return (MUFU_MASK >> (g & 15)) & 1u; }

__device__ __align__(1024) bf16 g_qkv[96 * (HEAD_BYTES / 2)];
constexpr int WT_WO = 0, WT_W1 = WT_WO + 80 * 10240, WT_W2 = WT_W1 + 160 * 14336, WT_QKV = WT_W2 + 144 * 15360, WT_END = WT_QKV + 160 * 16384;
__device__ __align__(1024) uint8_t g_wt[WT_END];
__device__ __forceinline__ int x_line(int row, int cg) { return (((row >> 7) * 10 + (cg >> 3)) * 16 + ((row >> 3) & 15)) * 8 + (cg & 7); }
__device__ __forceinline__ int o_line(int row, int cg) { return (((row >> 6) * 10 + (cg >> 3)) * 8 + ((row >> 3) & 7)) * 8 + (cg & 7); }
__device__ __forceinline__ int h_line(int row, int cg) { return (((row >> 6) * 18 + cg / 12) * 8 + ((row >> 3) & 7)) * 12 + cg % 12; }
__device__ __align__(1024) bf16 g_x0[SEQ * DM];
__device__ __align__(1024) bf16 g_o[SEQ * DM];
__device__ __align__(1024) bf16 g_x1[SEQ * DM];
__device__ __align__(1024) bf16 g_x2[SEQ * DM];
__device__ __align__(1024) bf16 g_h[SEQ * FF];
constexpr int FLAG_SET = 320, NORM_OFF = 256;
struct Small {
  float2 st0[2 * SEQ];
  float2 st1[8 * SEQ];
  float2 st2[8 * SEQ];
  float csp_w1[10 * 1792];
  float cs_qkv[1920];
  unsigned int flags[3 * FLAG_SET];
  uint32_t zeros[4];
};
__device__ __align__(1024) Small g_s;

__device__ __forceinline__ uint32_t smem_u32(const void* p) { return (uint32_t)__cvta_generic_to_shared(p); }
__device__ __forceinline__ void mbar_init(uint32_t bar, int cnt) { asm volatile("mbarrier.init.shared::cta.b64 [%0], %1;" ::"r"(bar), "r"(cnt) : "memory"); }
__device__ __forceinline__ void mbar_expect_tx(uint32_t bar, uint32_t bytes) { asm volatile("mbarrier.arrive.expect_tx.shared::cta.b64 _, [%0], %1;" ::"r"(bar), "r"(bytes) : "memory"); }
__device__ __forceinline__ void mbar_arrive(uint32_t bar) { asm volatile("mbarrier.arrive.shared::cta.b64 _, [%0];" ::"r"(bar) : "memory"); }
__device__ __forceinline__ bool mbar_try(uint32_t bar, uint32_t parity) {
  uint32_t ok;
  asm volatile("{\n.reg .pred p;\nmbarrier.try_wait.parity.shared::cta.b64 p, [%1], %2;\nselp.u32 %0, 1, 0, p;\n}\n" : "=r"(ok) : "r"(bar), "r"(parity) : "memory");
  return ok != 0;
}
__device__ __forceinline__ bool mbar_test(uint32_t bar, uint32_t parity) {
  uint32_t ok;
  asm volatile("{\n.reg .pred p;\nmbarrier.test_wait.parity.shared::cta.b64 p, [%1], %2;\nselp.u32 %0, 1, 0, p;\n}\n" : "=r"(ok) : "r"(bar), "r"(parity) : "memory");
  return ok != 0;
}
__device__ __forceinline__ void mbar_wait(uint32_t bar, uint32_t parity) {
  if (mbar_try(bar, parity)) return;
#pragma unroll 1
  for (int it = 0; it < (1 << 22); it++)
    if (mbar_try(bar, parity)) return;
  __trap();
}
__device__ __forceinline__ void mbar_wait_warp(uint32_t bar, uint32_t parity) {
#pragma unroll 1
  for (int it = 0; !__all_sync(0xffffffffu, mbar_try(bar, parity)); it++)
    if (it > (1 << 22)) __trap();
}
__device__ __forceinline__ void flag_wait(const unsigned int* f, unsigned int target) {
  unsigned int v;
#pragma unroll 1
  for (int it = 0; it < (1 << 22); it++) {
    asm volatile("ld.acquire.gpu.global.u32 %0, [%1];" : "=r"(v) : "l"(f) : "memory");
    if (v >= target) return;
  }
  __trap();
}
__device__ __forceinline__ void flag_signal(unsigned int* f) { asm volatile("red.release.gpu.global.add.u32 [%0], 1;" ::"l"(f) : "memory"); }
__device__ __forceinline__ void fence_async_global() { asm volatile("fence.proxy.async.global;" ::: "memory"); }
__device__ __forceinline__ void pdl_wait() { asm volatile("griddepcontrol.wait;" ::: "memory"); }
__device__ __forceinline__ void pdl_launch() { asm volatile("griddepcontrol.launch_dependents;" ::: "memory"); }
__device__ __forceinline__ void named_bar(int id, int n) { asm volatile("bar.sync %0, %1;" ::"r"(id), "r"(n) : "memory"); }
__device__ __forceinline__ void bulk_g2s(uint32_t dst, const void* src, uint32_t bytes, uint32_t bar) {
  asm volatile("cp.async.bulk.shared::cluster.global.mbarrier::complete_tx::bytes [%0], [%1], %2, [%3];" ::"r"(dst), "l"(src), "r"(bytes), "r"(bar) : "memory");
}
__device__ __forceinline__ void tma_2d(uint32_t dst, const CUtensorMap* m, int c0, int c1, uint32_t bar) {
  asm volatile("cp.async.bulk.tensor.2d.shared::cluster.global.mbarrier::complete_tx::bytes [%0], [%1, {%3, %4}], [%2];" ::"r"(dst), "l"(m), "r"(bar), "r"(c0), "r"(c1) : "memory");
}
__device__ __forceinline__ void tma_3d(uint32_t dst, const CUtensorMap* m, int c0, int c1, int c2, uint32_t bar) {
  asm volatile("cp.async.bulk.tensor.3d.shared::cluster.global.mbarrier::complete_tx::bytes [%0], [%1, {%3, %4, %5}], [%2];" ::"r"(dst), "l"(m), "r"(bar), "r"(c0), "r"(c1), "r"(c2) : "memory");
}
__device__ __forceinline__ void prefetch_map(const CUtensorMap* m) { asm volatile("prefetch.tensormap [%0];" ::"l"(m) : "memory"); }
__device__ __forceinline__ void wg_fence() { asm volatile("wgmma.fence.sync.aligned;" ::: "memory"); }
__device__ __forceinline__ void wg_commit() { asm volatile("wgmma.commit_group.sync.aligned;" ::: "memory"); }
template <int N> __device__ __forceinline__ void wg_wait() { asm volatile("wgmma.wait_group.sync.aligned %0;" ::"n"(N) : "memory"); }
template <int N> __device__ __forceinline__ void fence_regs(float (&d)[N]) {
#pragma unroll
  for (int i = 0; i < N; i++) asm volatile("" : "+f"(d[i])::"memory");
}
template <int N> __device__ __forceinline__ void fence_regs(uint32_t (&d)[N]) {
#pragma unroll
  for (int i = 0; i < N; i++) asm volatile("" : "+r"(d[i])::"memory");
}
__device__ __forceinline__ uint64_t mk_desc(uint32_t addr, uint32_t lbo, uint32_t sbo, uint64_t swz) {
  return (uint64_t)((addr & 0x3FFFF) >> 4) | ((uint64_t)(lbo >> 4) << 16) | ((uint64_t)(sbo >> 4) << 32) | (swz << 62);
}
__device__ __forceinline__ uint32_t pack_bf16(float lo, float hi) {
  uint32_t r;
  asm("cvt.rn.bf16x2.f32 %0, %1, %2;" : "=r"(r) : "f"(hi), "f"(lo));
  return r;
}
__device__ __forceinline__ float bf_lo(uint32_t v) { return __uint_as_float(v << 16); }
__device__ __forceinline__ float bf_hi(uint32_t v) { return __uint_as_float(v & 0xFFFF0000u); }
__device__ __forceinline__ float ex2(float x) { float r; asm("ex2.approx.ftz.f32 %0, %1;" : "=f"(r) : "f"(x)); return r; }

template<int TB> __device__ __forceinline__ void wgmma_rs_n24(float (&d)[12], uint32_t a0, uint32_t a1, uint32_t a2, uint32_t a3, uint64_t db, int sd) {
  asm volatile("{\n.reg .pred p;\nsetp.ne.b32 p, %17, 0;\n"
    "wgmma.mma_async.sync.aligned.m64n24k16.f32.bf16.bf16 "
    "{%0,%1,%2,%3,%4,%5,%6,%7,%8,%9,%10,%11}, "
    "{%12,%13,%14,%15}, %16, p, 1, 1, %18;\n}\n"
    : "+f"(d[0]),"+f"(d[1]),"+f"(d[2]),"+f"(d[3]),"+f"(d[4]),"+f"(d[5]),"+f"(d[6]),"+f"(d[7]),"+f"(d[8]),"+f"(d[9]),"+f"(d[10]),"+f"(d[11])
    : "r"(a0), "r"(a1), "r"(a2), "r"(a3), "l"(db), "r"(sd), "n"(TB));
}
template<int TB> __device__ __forceinline__ void wgmma_rs_n120(float (&d)[60], uint32_t a0, uint32_t a1, uint32_t a2, uint32_t a3, uint64_t db, int sd) {
  asm volatile("{\n.reg .pred p;\nsetp.ne.b32 p, %65, 0;\n"
    "wgmma.mma_async.sync.aligned.m64n120k16.f32.bf16.bf16 "
    "{%0,%1,%2,%3,%4,%5,%6,%7,%8,%9,%10,%11,%12,%13,%14,%15,%16,%17,%18,%19,%20,%21,%22,%23,%24,%25,%26,%27,%28,%29,%30,%31,%32,%33,%34,%35,%36,%37,%38,%39,%40,%41,%42,%43,%44,%45,%46,%47,%48,%49,%50,%51,%52,%53,%54,%55,%56,%57,%58,%59}, "
    "{%60,%61,%62,%63}, %64, p, 1, 1, %66;\n}\n"
    : "+f"(d[0]),"+f"(d[1]),"+f"(d[2]),"+f"(d[3]),"+f"(d[4]),"+f"(d[5]),"+f"(d[6]),"+f"(d[7]),"+f"(d[8]),"+f"(d[9]),"+f"(d[10]),"+f"(d[11]),"+f"(d[12]),"+f"(d[13]),"+f"(d[14]),"+f"(d[15]),"+f"(d[16]),"+f"(d[17]),"+f"(d[18]),"+f"(d[19]),"+f"(d[20]),"+f"(d[21]),"+f"(d[22]),"+f"(d[23]),"+f"(d[24]),"+f"(d[25]),"+f"(d[26]),"+f"(d[27]),"+f"(d[28]),"+f"(d[29]),"+f"(d[30]),"+f"(d[31]),"+f"(d[32]),"+f"(d[33]),"+f"(d[34]),"+f"(d[35]),"+f"(d[36]),"+f"(d[37]),"+f"(d[38]),"+f"(d[39]),"+f"(d[40]),"+f"(d[41]),"+f"(d[42]),"+f"(d[43]),"+f"(d[44]),"+f"(d[45]),"+f"(d[46]),"+f"(d[47]),"+f"(d[48]),"+f"(d[49]),"+f"(d[50]),"+f"(d[51]),"+f"(d[52]),"+f"(d[53]),"+f"(d[54]),"+f"(d[55]),"+f"(d[56]),"+f"(d[57]),"+f"(d[58]),"+f"(d[59])
    : "r"(a0), "r"(a1), "r"(a2), "r"(a3), "l"(db), "r"(sd), "n"(TB));
}
template<int TB> __device__ __forceinline__ void wgmma_rs_n128(float (&d)[64], uint32_t a0, uint32_t a1, uint32_t a2, uint32_t a3, uint64_t db, int sd) {
  asm volatile("{\n.reg .pred p;\nsetp.ne.b32 p, %69, 0;\n"
    "wgmma.mma_async.sync.aligned.m64n128k16.f32.bf16.bf16 "
    "{%0,%1,%2,%3,%4,%5,%6,%7,%8,%9,%10,%11,%12,%13,%14,%15,%16,%17,%18,%19,%20,%21,%22,%23,%24,%25,%26,%27,%28,%29,%30,%31,%32,%33,%34,%35,%36,%37,%38,%39,%40,%41,%42,%43,%44,%45,%46,%47,%48,%49,%50,%51,%52,%53,%54,%55,%56,%57,%58,%59,%60,%61,%62,%63}, "
    "{%64,%65,%66,%67}, %68, p, 1, 1, %70;\n}\n"
    : "+f"(d[0]),"+f"(d[1]),"+f"(d[2]),"+f"(d[3]),"+f"(d[4]),"+f"(d[5]),"+f"(d[6]),"+f"(d[7]),"+f"(d[8]),"+f"(d[9]),"+f"(d[10]),"+f"(d[11]),"+f"(d[12]),"+f"(d[13]),"+f"(d[14]),"+f"(d[15]),"+f"(d[16]),"+f"(d[17]),"+f"(d[18]),"+f"(d[19]),"+f"(d[20]),"+f"(d[21]),"+f"(d[22]),"+f"(d[23]),"+f"(d[24]),"+f"(d[25]),"+f"(d[26]),"+f"(d[27]),"+f"(d[28]),"+f"(d[29]),"+f"(d[30]),"+f"(d[31]),"+f"(d[32]),"+f"(d[33]),"+f"(d[34]),"+f"(d[35]),"+f"(d[36]),"+f"(d[37]),"+f"(d[38]),"+f"(d[39]),"+f"(d[40]),"+f"(d[41]),"+f"(d[42]),"+f"(d[43]),"+f"(d[44]),"+f"(d[45]),"+f"(d[46]),"+f"(d[47]),"+f"(d[48]),"+f"(d[49]),"+f"(d[50]),"+f"(d[51]),"+f"(d[52]),"+f"(d[53]),"+f"(d[54]),"+f"(d[55]),"+f"(d[56]),"+f"(d[57]),"+f"(d[58]),"+f"(d[59]),"+f"(d[60]),"+f"(d[61]),"+f"(d[62]),"+f"(d[63])
    : "r"(a0), "r"(a1), "r"(a2), "r"(a3), "l"(db), "r"(sd), "n"(TB));
}
__device__ __forceinline__ void wgmma_ss(float (&d)[40], uint64_t da, uint64_t db, int sd) {
  asm volatile("{\n.reg .pred p;\nsetp.ne.b32 p, %42, 0;\n"
    "wgmma.mma_async.sync.aligned.m64n80k16.f32.bf16.bf16 "
    "{%0,%1,%2,%3,%4,%5,%6,%7,%8,%9,%10,%11,%12,%13,%14,%15,%16,%17,%18,%19,%20,%21,%22,%23,%24,%25,%26,%27,%28,%29,%30,%31,%32,%33,%34,%35,%36,%37,%38,%39}, "
    "%40, %41, p, 1, 1, 0, 1;\n}\n"
    : "+f"(d[0]),"+f"(d[1]),"+f"(d[2]),"+f"(d[3]),"+f"(d[4]),"+f"(d[5]),"+f"(d[6]),"+f"(d[7]),"+f"(d[8]),"+f"(d[9]),"+f"(d[10]),"+f"(d[11]),"+f"(d[12]),"+f"(d[13]),"+f"(d[14]),"+f"(d[15]),"+f"(d[16]),"+f"(d[17]),"+f"(d[18]),"+f"(d[19]),"+f"(d[20]),"+f"(d[21]),"+f"(d[22]),"+f"(d[23]),"+f"(d[24]),"+f"(d[25]),"+f"(d[26]),"+f"(d[27]),"+f"(d[28]),"+f"(d[29]),"+f"(d[30]),"+f"(d[31]),"+f"(d[32]),"+f"(d[33]),"+f"(d[34]),"+f"(d[35]),"+f"(d[36]),"+f"(d[37]),"+f"(d[38]),"+f"(d[39])
    : "l"(da), "l"(db), "r"(sd));
}
__device__ __forceinline__ void wgmma_ss(float (&d)[56], uint64_t da, uint64_t db, int sd) {
  asm volatile("{\n.reg .pred p;\nsetp.ne.b32 p, %58, 0;\n"
    "wgmma.mma_async.sync.aligned.m64n112k16.f32.bf16.bf16 "
    "{%0,%1,%2,%3,%4,%5,%6,%7,%8,%9,%10,%11,%12,%13,%14,%15,%16,%17,%18,%19,%20,%21,%22,%23,%24,%25,%26,%27,%28,%29,%30,%31,%32,%33,%34,%35,%36,%37,%38,%39,%40,%41,%42,%43,%44,%45,%46,%47,%48,%49,%50,%51,%52,%53,%54,%55}, "
    "%56, %57, p, 1, 1, 0, 1;\n}\n"
    : "+f"(d[0]),"+f"(d[1]),"+f"(d[2]),"+f"(d[3]),"+f"(d[4]),"+f"(d[5]),"+f"(d[6]),"+f"(d[7]),"+f"(d[8]),"+f"(d[9]),"+f"(d[10]),"+f"(d[11]),"+f"(d[12]),"+f"(d[13]),"+f"(d[14]),"+f"(d[15]),"+f"(d[16]),"+f"(d[17]),"+f"(d[18]),"+f"(d[19]),"+f"(d[20]),"+f"(d[21]),"+f"(d[22]),"+f"(d[23]),"+f"(d[24]),"+f"(d[25]),"+f"(d[26]),"+f"(d[27]),"+f"(d[28]),"+f"(d[29]),"+f"(d[30]),"+f"(d[31]),"+f"(d[32]),"+f"(d[33]),"+f"(d[34]),"+f"(d[35]),"+f"(d[36]),"+f"(d[37]),"+f"(d[38]),"+f"(d[39]),"+f"(d[40]),"+f"(d[41]),"+f"(d[42]),"+f"(d[43]),"+f"(d[44]),"+f"(d[45]),"+f"(d[46]),"+f"(d[47]),"+f"(d[48]),"+f"(d[49]),"+f"(d[50]),"+f"(d[51]),"+f"(d[52]),"+f"(d[53]),"+f"(d[54]),"+f"(d[55])
    : "l"(da), "l"(db), "r"(sd));
}
__device__ __forceinline__ void wgmma_ss(float (&d)[60], uint64_t da, uint64_t db, int sd) {
  asm volatile("{\n.reg .pred p;\nsetp.ne.b32 p, %62, 0;\n"
    "wgmma.mma_async.sync.aligned.m64n120k16.f32.bf16.bf16 "
    "{%0,%1,%2,%3,%4,%5,%6,%7,%8,%9,%10,%11,%12,%13,%14,%15,%16,%17,%18,%19,%20,%21,%22,%23,%24,%25,%26,%27,%28,%29,%30,%31,%32,%33,%34,%35,%36,%37,%38,%39,%40,%41,%42,%43,%44,%45,%46,%47,%48,%49,%50,%51,%52,%53,%54,%55,%56,%57,%58,%59}, "
    "%60, %61, p, 1, 1, 0, 1;\n}\n"
    : "+f"(d[0]),"+f"(d[1]),"+f"(d[2]),"+f"(d[3]),"+f"(d[4]),"+f"(d[5]),"+f"(d[6]),"+f"(d[7]),"+f"(d[8]),"+f"(d[9]),"+f"(d[10]),"+f"(d[11]),"+f"(d[12]),"+f"(d[13]),"+f"(d[14]),"+f"(d[15]),"+f"(d[16]),"+f"(d[17]),"+f"(d[18]),"+f"(d[19]),"+f"(d[20]),"+f"(d[21]),"+f"(d[22]),"+f"(d[23]),"+f"(d[24]),"+f"(d[25]),"+f"(d[26]),"+f"(d[27]),"+f"(d[28]),"+f"(d[29]),"+f"(d[30]),"+f"(d[31]),"+f"(d[32]),"+f"(d[33]),"+f"(d[34]),"+f"(d[35]),"+f"(d[36]),"+f"(d[37]),"+f"(d[38]),"+f"(d[39]),"+f"(d[40]),"+f"(d[41]),"+f"(d[42]),"+f"(d[43]),"+f"(d[44]),"+f"(d[45]),"+f"(d[46]),"+f"(d[47]),"+f"(d[48]),"+f"(d[49]),"+f"(d[50]),"+f"(d[51]),"+f"(d[52]),"+f"(d[53]),"+f"(d[54]),"+f"(d[55]),"+f"(d[56]),"+f"(d[57]),"+f"(d[58]),"+f"(d[59])
    : "l"(da), "l"(db), "r"(sd));
}


constexpr int PH_WO = 1, PH_W1 = 2, PH_W2 = 4, PH_QKV = 8;
constexpr int SA = 4, SB = 10, STAGE = 16384;
constexpr int SM_B = SA * STAGE;
constexpr int SM_CS = SM_B + SB * STAGE;
constexpr int SM_B1 = SM_CS + 448;
constexpr int SM_ROW = SM_B1 + 224;
constexpr int SM_BAR = SM_ROW + 2048;
constexpr int CHAIN_SMEM = SM_BAR + 344;
static_assert(CHAIN_SMEM <= 232448, "shared memory");
constexpr int CHAIN_THREADS = 352;
constexpr int BAR_FA = 0, BAR_EA = SA * 8, BAR_FB = 2 * SA * 8, BAR_EB = (2 * SA + SB) * 8, BAR_AUX = (2 * SA + 2 * SB) * 8, BAR_JOB = BAR_AUX + 32,
              BAR_FH = BAR_JOB, BAR_EH = BAR_JOB + 40, BAR_TILE = BAR_JOB + 80;

struct alignas(64) ChainParams {
  CUtensorMap a_x, b_wo, b_w1, b_wqkv, o_out;
  const bf16* xres;
  const bf16* xin;
  const bf16 *b1, *b2;
  unsigned int* flags;
  signed char pref[160];
};

template <int V> struct IC { static constexpr int value = V; };
struct Ring { uint32_t s, ph; };
template <int N> __device__ __forceinline__ void ring_adv(Ring& r) { if (++r.s == N) { r.s = 0; r.ph ^= 1; } }

template <int KT, int BYTES, int N, int STRIDE = STAGE, int LIM = 0>
__device__ __forceinline__ void produce(const void* src, uint32_t dst, uint32_t full, uint32_t empty, Ring& r) {
#pragma unroll 1
  for (int kt = 0; kt < KT; kt++) {
    if constexpr (LIM > 0) mbar_wait(full + (r.s >= LIM ? r.s - LIM : r.s + N - LIM) * 8, r.s >= LIM ? r.ph : r.ph ^ 1);
    mbar_wait(empty + r.s * 8, r.ph ^ 1);
    mbar_expect_tx(full + r.s * 8, BYTES);
    bulk_g2s(dst + r.s * STRIDE, (const uint8_t*)src + kt * BYTES, BYTES, full + r.s * 8);
    ring_adv<N>(r);
  }
}
template <int BYTES> __device__ __forceinline__ void produce_first(const void* src, uint32_t dst, uint32_t full, uint32_t empty, Ring& r) {
  produce<9, BYTES, SB>(src, dst, full, empty, r);
  produce<10 - 9, BYTES, SB, STAGE, 9>((const uint8_t*)src + 9 * BYTES, dst, full, empty, r);
}
__device__ __forceinline__ void bulk_s2g(void* dst, uint32_t src, uint32_t bytes) {
  asm volatile("cp.async.bulk.global.shared::cta.bulk_group [%0], [%1], %2;\ncp.async.bulk.commit_group;" ::"l"(dst), "r"(src), "r"(bytes) : "memory");
}
template <int BK, bool B128> __device__ __forceinline__ uint64_t b_desc(uint32_t addr) { return B128 ? mk_desc(addr, 8192, 1024, 1) : mk_desc(addr, BK * 32, 256, 3); }

template <int BN, int MT, int KT, int BK, int APT, bool TILED, bool B128, bool HR = false>
__device__ __forceinline__ void mainloop(float (&acc)[MT][BN / 2], uint32_t sbase, uint32_t bars, int lane, int wg, int a0, bool pass, Ring& rb, int cont = 0) {
  constexpr int NA = HR ? 5 : SA, AST = HR ? 12288 : STAGE, FA = HR ? BAR_FH : BAR_FA, EA = HR ? BAR_EH : BAR_EA;
  Ring ra{(uint32_t)a0 % NA, ((uint32_t)a0 / NA) & 1};
#pragma unroll
  for (int m = 0; m < MT; m++) fence_regs(acc[m]);
  if (HR || a0 != 0) named_bar(6 - wg, 256);
  mbar_wait(bars + BAR_FB + rb.s * 8, rb.ph);
  mbar_wait(bars + FA + ra.s * 8, ra.ph);
  const uint64_t da0 = TILED ? mk_desc(sbase, 128, BK * 16, 0) : mk_desc(sbase, 16, 1024, 1), db0 = b_desc<BK, B128>(sbase + SM_B);
  uint32_t relA = 0, relB = 0;
#pragma unroll 1
  for (int kt = 0; kt < KT; kt += APT) {
#pragma unroll
    for (int u = 0; u < APT; u++) {
      const bool more = u + 1 < APT || kt + APT < KT;
      if (!more && pass) asm volatile("bar.arrive %0, 256;" ::"r"(5 + wg) : "memory");
      const uint64_t da = da0 + ra.s * (AST / 16) + u * 512, db = db0 + rb.s * (STAGE / 16);
      wg_fence();
#pragma unroll
      for (int k = 0; k < BK / 16; k++)
#pragma unroll
        for (int m = 0; m < MT; m++) wgmma_ss(acc[m], da + m * 512 + k * (TILED ? 16 : 2), db + k * (B128 ? 128 : 32), (kt | u | k | cont) != 0);
      wg_commit();
      const uint32_t curA = u == APT - 1 ? bars + EA + ra.s * 8 : 0, curB = bars + BAR_EB + rb.s * 8;
      if (u == APT - 1) ring_adv<NA>(ra);
      ring_adv<SB>(rb);
      bool ok = mbar_test(bars + BAR_FB + rb.s * 8, rb.ph);
      if (u == APT - 1) ok &= mbar_test(bars + FA + ra.s * 8, ra.ph);
      wg_wait<1>();
      if (lane == 0 && relB) { if (relA) mbar_arrive(relA); mbar_arrive(relB); }
      relA = curA; relB = curB;
      if (!ok && more) { mbar_wait(bars + BAR_FB + rb.s * 8, rb.ph); mbar_wait(bars + FA + ra.s * 8, ra.ph); }
    }
  }
  wg_wait<0>();
#pragma unroll
  for (int m = 0; m < MT; m++) fence_regs(acc[m]);
  if (lane == 0) { mbar_arrive(relA); mbar_arrive(relB); }
}
__device__ __forceinline__ void acquire_stage(uint32_t bars, const Ring& rb, uint32_t s) { mbar_wait(bars + BAR_EB + s * 8, s >= rb.s ? rb.ph ^ 1 : rb.ph); }

template <bool FINAL>
__device__ __forceinline__ void epi_resid(const float (&acc)[40], uint32_t (&res)[20], bf16* out, float2* st, uint8_t* stage, int row0, int j, int lane) {
  const int q = lane & 3;
  uint32_t* o0 = FINAL ? (uint32_t*)(stage + (row0 & 63) * 160) + q : (uint32_t*)out + lane;
  float s0 = 0.f, t0 = 0.f, s1 = 0.f, t1 = 0.f;
#pragma unroll
  for (int b = 0; b < 10; b++) {
    res[2 * b] = pack_bf16(acc[4 * b], acc[4 * b + 1]);
    res[2 * b + 1] = pack_bf16(acc[4 * b + 2], acc[4 * b + 3]);
    if (FINAL) { o0[b * 4] = res[2 * b]; o0[b * 4 + 320] = res[2 * b + 1]; }
    else { const int ln = x_line(row0, j * 10 + b); o0[ln * 32] = res[2 * b]; o0[ln * 32 + 256] = res[2 * b + 1]; }
  }
  if (!FINAL) {
#pragma unroll
    for (int b = 0; b < 10; b++) {
      s0 += acc[4 * b] + acc[4 * b + 1]; t0 = fmaf(acc[4 * b], acc[4 * b], fmaf(acc[4 * b + 1], acc[4 * b + 1], t0));
      s1 += acc[4 * b + 2] + acc[4 * b + 3]; t1 = fmaf(acc[4 * b + 2], acc[4 * b + 2], fmaf(acc[4 * b + 3], acc[4 * b + 3], t1));
    }
#pragma unroll
    for (int m = 1; m < 4; m <<= 1) {
      s0 += __shfl_xor_sync(0xffffffffu, s0, m); t0 += __shfl_xor_sync(0xffffffffu, t0, m);
      s1 += __shfl_xor_sync(0xffffffffu, s1, m); t1 += __shfl_xor_sync(0xffffffffu, t1, m);
    }
    if (q < 2) st[j * SEQ + row0 + q * 8] = q ? make_float2(s1, t1) : make_float2(s0, t0);
  }
}
__device__ __forceinline__ void publish(unsigned int* f, int wg, int tid) {
  named_bar(2 + wg, 128);
  if ((tid & 127) == 0) flag_signal(f);
}
__device__ __forceinline__ float gelu_half(float s) {
  const float z = s * fmaf(s * s, 8.f * 0.044715f * 0.7978845608028654f, 2.f * 0.7978845608028654f);
  float th;
  asm("tanh.approx.f32 %0, %1;" : "=f"(th) : "f"(z));
  return fmaf(s, th, s);
}
template <bool DOUBLE> __device__ __forceinline__ float2 row_coef(float s, float t) {
  const float mean = s * (1.f / DM);
  const float var = fmaxf(fmaf(-mean, mean, t * (1.f / DM)), 0.f);
  float r = rsqrtf(var + LN_EPS);
  if (DOUBLE) r *= 0.5f * rsqrtf(var * r * r + LN_EPS);
  return make_float2(r, -r * mean);
}
template <bool DOUBLE, int NP> __device__ __forceinline__ void reduce_stats(const float2* st, float2* dst, int i, int lane) {
  float4 v[2][NP];
#pragma unroll
  for (int rr = 0; rr < 2; rr++)
#pragma unroll
    for (int k = 0; k < NP; k++) v[rr][k] = __ldcg((const float4*)(st + k * SEQ + i * 128 + rr * 64) + lane);
#pragma unroll
  for (int rr = 0; rr < 2; rr++) {
    float s0 = 0.f, t0 = 0.f, s1 = 0.f, t1 = 0.f;
#pragma unroll
    for (int k = 0; k < NP; k++) { s0 += v[rr][k].x; t0 += v[rr][k].y; s1 += v[rr][k].z; t1 += v[rr][k].w; }
    dst[rr * 64 + lane * 2] = row_coef<DOUBLE>(s0, t0);
    dst[rr * 64 + lane * 2 + 1] = row_coef<DOUBLE>(s1, t1);
  }
}

template <int PH, bool FIRST, bool LAST>
__global__ void __launch_bounds__(CHAIN_THREADS, 1) chain_kernel(const __grid_constant__ ChainParams p) {
  extern __shared__ __align__(1024) uint8_t smem[];
  const uint32_t sbase = smem_u32(smem), bars = sbase + SM_BAR;
  float* cs = (float*)(smem + SM_CS);
  uint32_t* sb1 = (uint32_t*)(smem + SM_B1);
  const int tid = threadIdx.x, lane = tid & 31, warp = __shfl_sync(0xffffffffu, tid >> 5, 0);
  if (tid == 32) {
    unsigned int* claim = p.flags + 64;
    uint32_t smid;
    asm volatile("mov.u32 %0, %%smid;" : "=r"(smid));
    int t = smid < 160 ? p.pref[smid] : -1;
    if (t >= 0 && atomicExch(claim + t, 1u) != 0u) t = -2;
    if (t == -1) {
#pragma unroll 1
      for (int it = 0; it < 100000; it++) {
        if (*(volatile unsigned int*)(claim + 128) >= 128u) break;
        __nanosleep(200);
      }
    }
    if (t < 0) {
      t = -1;
      if (*(volatile unsigned int*)(claim + 128) < 128u) {
#pragma unroll 1
        for (int c = 0; c < 128 && t < 0; c++)
          if (atomicExch(claim + c, 1u) == 0u) t = c;
      }
    }
    if (t >= 0) atomicAdd(claim + 128, 1u);
    *(volatile int*)(smem + SM_BAR + BAR_TILE) = t;
  }
  unsigned int* fl = p.flags;
  if (tid == 0) {
    for (int s = 0; s < SA; s++) { mbar_init(bars + BAR_FA + s * 8, 1); mbar_init(bars + BAR_EA + s * 8, 4); }
    for (int s = 0; s < SB; s++) { mbar_init(bars + BAR_FB + s * 8, 1); mbar_init(bars + BAR_EB + s * 8, 8); }
    mbar_init(bars + BAR_AUX, 32); mbar_init(bars + BAR_AUX + 8, 32);
    mbar_init(bars + BAR_AUX + 16, FIRST ? 37 : 32); mbar_init(bars + BAR_AUX + 24, 32);
    for (int s = 0; s < 5; s++) { mbar_init(bars + BAR_FH + s * 8, 1); mbar_init(bars + BAR_EH + s * 8, 4); }
    asm volatile("fence.mbarrier_init.release.cluster;" ::: "memory");
  }
  if (tid == 256) {
    if (FIRST) {
      uint32_t smid;
      asm volatile("mov.u32 %0, %%smid;" : "=r"(smid));
      const int t = smid < 160 ? p.pref[smid] : -1;
      if (t >= 0) {
        asm volatile("cp.async.bulk.prefetch.tensor.2d.L2.global [%0, {%1, %2}];" ::"l"(&p.a_x), "r"(0), "r"((t >> 4) * 256) : "memory");
        asm volatile("cp.async.bulk.prefetch.tensor.3d.L2.global [%0, {%1, %2, %3}];" ::"l"(&p.b_wqkv), "r"(0), "r"(t & 15), "r"(0) : "memory");
        asm volatile("cp.async.bulk.prefetch.tensor.3d.L2.global [%0, {%1, %2, %3}];" ::"l"(&p.b_wqkv), "r"(64), "r"(t & 15), "r"(0) : "memory");
      }
      prefetch_map(&p.b_w1); prefetch_map(&p.b_wo);
    }
    if (LAST) prefetch_map(&p.o_out);
  }
  __syncthreads();
  pdl_launch();
  const int tile = *(volatile int*)(smem + SM_BAR + BAR_TILE);
  if (tile < 0) return;
  const int g = tile >> 4, c = tile & 15;

  if (warp == 9) {
    if (lane == 0) {
      if (FIRST) {
#pragma unroll 1
        for (int kt = 0; kt < 10; kt++) {
          if (kt >= 4) mbar_wait(bars + BAR_FB + (kt - 4) * 8, 0);
          mbar_expect_tx(bars + BAR_FB + kt * 8, STAGE);
          tma_3d(sbase + SM_B + kt * STAGE, &p.b_wqkv, 0, c, kt * 64, bars + BAR_FB + kt * 8);
          tma_3d(sbase + SM_B + kt * STAGE + 8192, &p.b_wqkv, 64, c, kt * 64, bars + BAR_FB + kt * 8);
        }
#pragma unroll 1
        for (int kt = g; kt < 10; kt += 8) {
          mbar_wait(bars + BAR_FB + kt * 8, 0);
          bulk_s2g(g_wt + WT_QKV + (c * 10 + kt) * STAGE, sbase + SM_B + kt * STAGE, STAGE);
        }
        asm volatile("cp.async.bulk.wait_group.read 0;" ::: "memory");
        mbar_arrive(bars + BAR_AUX + 16);
        asm volatile("cp.async.bulk.wait_group 0;" ::: "memory");
      } else {
        Ring r{0, 0};
        produce_first<10240>(g_wt + WT_WO + (c >> 1) * 10 * 10240, sbase + SM_B, bars + BAR_FB, bars + BAR_EB, r);
        produce<10, 14336, SB, STAGE, 2>(g_wt + WT_W1 + c * 10 * 14336, sbase + SM_B, bars + BAR_FB, bars + BAR_EB, r);
        pdl_wait();
        produce<18, 15360, SB, STAGE, 3>(g_wt + WT_W2 + (c >> 1) * 18 * 15360, sbase + SM_B, bars + BAR_FB, bars + BAR_EB, r);
        if (PH & PH_QKV) produce<10, STAGE, SB, STAGE, 2>(g_wt + WT_QKV + c * 10 * STAGE, sbase + SM_B, bars + BAR_FB, bars + BAR_EB, r);
      }
    }
  } else if (warp == 8) {
    if (lane == 0) {
      Ring r{0, 0};
      if (FIRST) {
#pragma unroll 1
        for (int t = 0; t < 20; t++) {
          mbar_wait(bars + BAR_EA + r.s * 8, r.ph ^ 1);
          mbar_expect_tx(bars + BAR_FA + r.s * 8, STAGE);
          tma_2d(sbase + r.s * STAGE, &p.a_x, (t % 10) * 64, g * 256 + (t / 10) * 128, bars + BAR_FA + r.s * 8);
          ring_adv<SA>(r);
        }
#pragma unroll 1
        for (int job = tile; job < 240; job += 128) {
          const int n = job >> 7;
          mbar_wait(bars + BAR_EB + (3 + n) * 8, 0);
          mbar_expect_tx(bars + BAR_JOB + n * 8, job < 160 ? 14336 : 10240);
#pragma unroll 1
          for (int b = 0; b < (job < 160 ? 7 : 5); b++)
            tma_3d(sbase + SM_B + (3 + n) * STAGE + b * 2048, job < 160 ? &p.b_w1 : &p.b_wo, (job < 160 ? ((job / 10) & 1) * 112 : 0) + b * 16,
                   job < 160 ? job / 20 : job / 10 - 16, (job % 10) * 64, bars + BAR_JOB + n * 8);
        }
#pragma unroll 1
        for (int job = tile; job < 240; job += 128) {
          mbar_wait(bars + BAR_JOB + (job >> 7) * 8, 0);
          bulk_s2g(g_wt + (job < 160 ? WT_W1 + job * 14336 : WT_WO + (job - 160) * 10240), sbase + SM_B + (3 + (job >> 7)) * STAGE, job < 160 ? 14336 : 10240);
        }
        asm volatile("cp.async.bulk.wait_group 0;" ::: "memory");
      } else {
#pragma unroll 1
        for (int s = 0; s < 2; s++) {
          if (s == 0) { pdl_wait(); }
          produce<5, 16384, SA>((const uint8_t*)g_o + (g * 4 + s * 2 + (c & 1)) * 10 * 8192, sbase, bars + BAR_FA, bars + BAR_EA, r);
        }
#pragma unroll 1
        for (int s = 0; s < 2; s++) {
          flag_wait(fl + g * 2 + s, 16); fence_async_global();
          produce<10, 16384, SA>((const uint8_t*)g_x1 + (g * 2 + s) * 10 * 16384, sbase, bars + BAR_FA, bars + BAR_EA, r);
        }
        Ring rh{0, 0};
#pragma unroll 1
        for (int s = 0; s < SA; s++) mbar_wait(bars + BAR_EA + s * 8, s >= r.s ? r.ph ^ 1 : r.ph);
        const uint8_t* hsrc = (const uint8_t*)g_h + (g * 4 + (c & 1)) * 18 * 12288;
#pragma unroll 1
        for (int s = 0; s < 2; s++) {
          flag_wait(fl + 16 + g * 2 + s, 16); fence_async_global();
          produce<10, 12288, 5, 12288>(hsrc + s * 36 * 12288, sbase, bars + BAR_FH, bars + BAR_EH, rh);
        }
#pragma unroll 1
        for (int s = 0; s < 2; s++) produce<8, 12288, 5, 12288>(hsrc + (s * 36 + 10) * 12288, sbase, bars + BAR_FH, bars + BAR_EH, rh);
        if (PH & PH_QKV) {
#pragma unroll 1
          for (int s = 0; s < 5; s++) mbar_wait(bars + BAR_EH + s * 8, s >= rh.s ? rh.ph ^ 1 : rh.ph);
        }
        if (PH & PH_QKV) {
#pragma unroll 1
          for (int s = 0; s < 2; s++) {
            flag_wait(fl + 32 + g * 2 + s, 16); fence_async_global();
            produce<10, 16384, SA>((const uint8_t*)g_x2 + (g * 2 + s) * 10 * 16384, sbase, bars + BAR_FA, bars + BAR_EA, r);
          }
        }
      }
    }
  } else if (warp == 10) {
    float2* srow = (float2*)(smem + SM_ROW);
    if (FIRST) {
      named_bar(4, 160);
      if (lane == 0) flag_signal(fl + g * 2 + (c >> 3));
#pragma unroll 1
      for (int s = 0; s < 2; s++) {
        if (lane == 0) flag_wait(fl + g * 2 + s, 8);
        __syncwarp();
        reduce_stats<false, 2>(g_s.st0, srow + s * 128, g * 2 + s, lane);
        mbar_arrive(bars + BAR_AUX + 16 + s * 8);
      }
#pragma unroll 1
      for (int n = 0; n < 2; n++) {
        const int job = n * 128 + tile;
        if (job < 160) {
          mbar_wait(bars + BAR_JOB + n * 8, 0);
          const uint8_t* base = smem + SM_B + (3 + n) * STAGE + ((lane & 15) >> 1) * 2048 + (lane >> 4) * 1024;
          float a[8];
#pragma unroll
          for (int e = 0; e < 8; e++) a[e] = 0.f;
#pragma unroll 4
          for (int r = 0; r < 32; r++) {
            const uint4 v = *(const uint4*)(base + r * 32 + (((lane & 1) ^ ((r >> 2) & 1)) * 16));
            a[0] += bf_lo(v.x); a[1] += bf_hi(v.x); a[2] += bf_lo(v.y); a[3] += bf_hi(v.y);
            a[4] += bf_lo(v.z); a[5] += bf_hi(v.z); a[6] += bf_lo(v.w); a[7] += bf_hi(v.w);
          }
#pragma unroll
          for (int e = 0; e < 8; e++) a[e] += __shfl_xor_sync(0xffffffffu, a[e], 16);
          if (lane < 14) {
            float4* d = (float4*)(g_s.csp_w1 + (job % 10) * 1792 + (job / 10) * 112 + lane * 8);
            d[0] = make_float4(a[0], a[1], a[2], a[3]); d[1] = make_float4(a[4], a[5], a[6], a[7]);
          }
        }
      }
    } else {
      if (lane < 28) {
        float4 v[10], a = make_float4(0.f, 0.f, 0.f, 0.f);
#pragma unroll
        for (int k = 0; k < 10; k++) v[k] = __ldcg((const float4*)(g_s.csp_w1 + k * 1792 + c * 112) + lane);
#pragma unroll
        for (int k = 0; k < 10; k++) { a.x += v[k].x; a.y += v[k].y; a.z += v[k].z; a.w += v[k].w; }
        ((float4*)cs)[lane] = a;
      }
      for (int k = lane; k < 56; k += 32) {
        const int col = (c >> 1) * 216 + (c & 1) * 112 + k * 2;
        const uint32_t v = col < FF ? __ldg((const uint32_t*)(p.b1 + col)) : 0u;
        sb1[k] = pack_bf16(0.5f * bf_lo(v), 0.5f * bf_hi(v));
      }
#pragma unroll 1
      for (int s = 0; s < 2; s++) {
        if (lane == 0) flag_wait(fl + g * 2 + s, 16);
        __syncwarp();
        reduce_stats<true, 8>(g_s.st1, srow + s * 128, g * 2 + s, lane);
        mbar_arrive(bars + BAR_AUX + s * 8);
      }
      if (PH & PH_QKV) {
        const float4 cq = lane < 30 ? __ldcg((const float4*)(g_s.cs_qkv + c * 120) + lane) : make_float4(0.f, 0.f, 0.f, 0.f);
#pragma unroll 1
        for (int s = 0; s < 2; s++) {
          if (lane == 0) { if (s == 0) flag_wait(fl + 16 + g * 2 + 1, 16); flag_wait(fl + 32 + g * 2 + s, 16); }
          __syncwarp();
          if (s == 0 && lane < 30) ((float4*)cs)[lane] = cq;
          reduce_stats<false, 8>(g_s.st2, srow + s * 128, g * 2 + s, lane);
          mbar_arrive(bars + BAR_AUX + 16 + s * 8);
        }
      }
    }
  } else {
    const int wg = warp >> 2, w4 = warp & 3, q = lane & 3;
    const int rbk = g * 2 + wg, rl = w4 * 16 + (lane >> 2);
    const int rowS = rbk * 128 + (c & 1) * 64 + rl, jS = c >> 1;
    const float2* srow = (const float2*)(smem + SM_ROW) + wg * 128;
    const bool t0 = (tid & 127) == 0;
    Ring rb{0, 0};
    uint32_t res[20];
    if (FIRST) {
      if (wg == 1) {
        const int xrow = g * 256 + c * 16 + (w4 & 1) * 8 + (lane >> 2), xcg = (w4 >> 1) * 40 + q;
        uint4 xv[10];
#pragma unroll
        for (int k = 0; k < 10; k++) xv[k] = __ldg((const uint4*)(p.xin + (size_t)xrow * DM) + xcg + k * 4);
        float xs = 0.f, xt = 0.f;
#pragma unroll
        for (int k = 0; k < 10; k++) {
          const uint32_t e[4] = {xv[k].x, xv[k].y, xv[k].z, xv[k].w};
#pragma unroll
          for (int m = 0; m < 4; m++) { const float a = bf_lo(e[m]), b = bf_hi(e[m]); xs += a + b; xt = fmaf(a, a, fmaf(b, b, xt)); }
        }
#pragma unroll
        for (int m = 1; m < 4; m <<= 1) { xs += __shfl_xor_sync(0xffffffffu, xs, m); xt += __shfl_xor_sync(0xffffffffu, xt, m); }
        if (q == 0) g_s.st0[(w4 >> 1) * SEQ + xrow] = make_float2(xs, xt);
        asm volatile("bar.arrive 4, 160;" ::: "memory");
#pragma unroll
        for (int k = 0; k < 10; k++) *((uint4*)g_x0 + x_line(xrow, xcg + k * 4) * 8 + (xrow & 7)) = xv[k];
        float o[60];
        const uint32_t one = 0x3F803F80u;
#pragma unroll 1
        for (int kt = 0; kt < 10; kt++) {
          mbar_wait(bars + BAR_FB + kt * 8, 0);
          wg_fence();
#pragma unroll
          for (int k = 0; k < 4; k++) wgmma_rs_n120<1>(o, one, one, one, one, b_desc<64, true>(sbase + SM_B + kt * STAGE) + k * 128, (kt | k) != 0);
          wg_commit();
        }
        wg_wait<0>();
        fence_regs(o);
        if ((tid & 127) < 4) {
#pragma unroll
          for (int b = 0; b < 15; b++) {
            *(float2*)(cs + b * 8 + q * 2) = make_float2(o[4 * b], o[4 * b + 1]);
            if (g == 0) *(float2*)(g_s.cs_qkv + c * 120 + b * 8 + q * 2) = make_float2(o[4 * b], o[4 * b + 1]);
          }
          mbar_arrive(bars + BAR_AUX + 16);
        }
        named_bar(3, 128);
      }
    } else {
#pragma unroll
      for (int b = 0; b < 10; b++) {
        const uint32_t* r0 = (const uint32_t*)p.xres + x_line(rowS, jS * 10 + b) * 32 + lane;
        res[2 * b] = __ldcg(r0); res[2 * b + 1] = __ldcg(r0 + 256);
      }
      {
        float acc[1][40];
#pragma unroll
        for (int b = 0; b < 20; b++) { acc[0][2 * b] = bf_lo(res[b]); acc[0][2 * b + 1] = bf_hi(res[b]); }
        mainloop<80, 1, 10, 64, 2, true, false>(acc, sbase, bars, lane, wg, wg * 5, wg != 0, rb, 1);
        epi_resid<false>(acc[0], res, g_x1, g_s.st1, smem, rowS, jS, lane);
        if (wg == 0) asm volatile("bar.arrive 5, 256;" ::: "memory");
        publish(fl + rbk, wg, tid);
      }
      {
        float acc[2][56];
        mainloop<112, 2, 10, 64, 1, true, false>(acc, sbase, bars, lane, wg, 10 + wg * 10, true, rb);
        mbar_wait(bars + BAR_AUX + wg * 8, 0);
        const float2 c0 = srow[rl], c1 = srow[rl + 8], c2 = srow[rl + 64], c3 = srow[rl + 72];
        const int cg0 = (c >> 1) * 27 + (c & 1) * 14;
        uint32_t* o0 = (uint32_t*)g_h + h_line(rbk * 128 + rl, cg0) * 32 + lane;
        int kg = cg0 % 12;
#pragma unroll
        for (int b = 0; b < 14; b++) {
          if (b < 13 || !(c & 1)) {
            const float2 cc = *(const float2*)(cs + b * 8 + q * 2);
            const uint32_t bb = sb1[b * 4 + q];
            const float bl = bf_lo(bb), bh = bf_hi(bb);
            o0[0] = pack_bf16(gelu_half(fmaf(c0.x, acc[0][4 * b], fmaf(c0.y, cc.x, bl))), gelu_half(fmaf(c0.x, acc[0][4 * b + 1], fmaf(c0.y, cc.y, bh))));
            o0[384] = pack_bf16(gelu_half(fmaf(c1.x, acc[0][4 * b + 2], fmaf(c1.y, cc.x, bl))), gelu_half(fmaf(c1.x, acc[0][4 * b + 3], fmaf(c1.y, cc.y, bh))));
            o0[18 * 3072] = pack_bf16(gelu_half(fmaf(c2.x, acc[1][4 * b], fmaf(c2.y, cc.x, bl))), gelu_half(fmaf(c2.x, acc[1][4 * b + 1], fmaf(c2.y, cc.y, bh))));
            o0[18 * 3072 + 384] = pack_bf16(gelu_half(fmaf(c3.x, acc[1][4 * b + 2], fmaf(c3.y, cc.x, bl))), gelu_half(fmaf(c3.x, acc[1][4 * b + 3], fmaf(c3.y, cc.y, bh))));
            o0 += (++kg == 12) ? (96 - 11) * 32 : 32;
            if (kg == 12) kg = 0;
          }
        }
        publish(fl + 16 + rbk, wg, tid);
      }
      {
        float acc[1][40];
#pragma unroll
        for (int b = 0; b < 10; b++) {
          const uint32_t bb = __ldg((const uint32_t*)(p.b2 + jS * 80) + b * 4 + q);
          acc[0][4 * b] = bf_lo(res[2 * b]) + bf_lo(bb); acc[0][4 * b + 1] = bf_hi(res[2 * b]) + bf_hi(bb);
          acc[0][4 * b + 2] = bf_lo(res[2 * b + 1]) + bf_lo(bb); acc[0][4 * b + 3] = bf_hi(res[2 * b + 1]) + bf_hi(bb);
        }
        mainloop<80, 1, 10, 96, 1, true, false, true>(acc, sbase, bars, lane, wg, wg * 10, true, rb, 1);
        mainloop<80, 1, 8, 96, 1, true, false, true>(acc, sbase, bars, lane, wg, 20 + wg * 8, LAST ? wg == 0 : wg != 0, rb, 1);
        if (LAST) {
          const uint32_t st = (rb.s + wg) % SB;
          acquire_stage(bars, rb, st);
          epi_resid<true>(acc[0], res, nullptr, nullptr, smem + SM_B + st * STAGE, rowS, jS, lane);
          asm volatile("fence.proxy.async.shared::cta;" ::: "memory");
          named_bar(2 + wg, 128);
          if (t0) {
            asm volatile("cp.async.bulk.tensor.2d.global.shared::cta.bulk_group [%0, {%2, %3}], [%1];" ::"l"(&p.o_out), "r"(sbase + SM_B + st * STAGE), "r"(jS * 80),
                         "r"(rbk * 128 + (c & 1) * 64) : "memory");
            asm volatile("cp.async.bulk.commit_group;\ncp.async.bulk.wait_group 0;" ::: "memory");
          }
        } else {
          epi_resid<false>(acc[0], res, g_x2, g_s.st2, smem, rowS, jS, lane);
          if (wg == 0) asm volatile("bar.arrive 5, 256;" ::: "memory");
          publish(fl + 32 + rbk, wg, tid);
        }
      }
    }
    if (PH & PH_QKV) {
      float acc[2][60];
      mainloop<120, 2, 10, 64, 1, !FIRST, true>(acc, sbase, bars, lane, wg, (FIRST ? 0 : 30) + wg * 10, wg == 0, rb);
      mbar_wait(bars + BAR_AUX + 16 + wg * 8, 0);
      pdl_wait();
      const float QS = 0.22360679774997896f * 1.4426950408889634f;
      unsigned int* smax = sb1 + 16 + wg * 8;
      if ((tid & 127) < 6) smax[tid & 127] = 0u;
      named_bar(2 + wg, 128);
      int off[5];
#pragma unroll
      for (int m = 0; m < 5; m++) {
        const int cc = m * 8 + q * 2, hh = cc >= 20, d = cc - hh * 20;
        off[m] = hh * 6144 + (d >> 3) * 128 + (d & 7) * 2;
      }
#pragma unroll
      for (int pr = 0; pr < 3; pr++) {
        const int part = (c * 6 + pr * 2) >> 5;
        float nrm[2];
        const uint32_t sst = (rb.s + pr) % SB, soff = wg ? pr * STAGE : SM_B + sst * STAGE;
        if (wg == 0) acquire_stage(bars, rb, sst);
        uint8_t* stg = smem + soff + w4 * 768 + (lane >> 2) * 16;
#pragma unroll
        for (int mt = 0; mt < 2; mt++) {
          const float2 c0 = srow[mt * 64 + rl], c1 = srow[mt * 64 + rl + 8];
          const bool mu0 = is_mufu(mt * 8 + w4 * 2), mu1 = is_mufu(mt * 8 + w4 * 2 + 1), mu = (q & 1) ? mu1 : mu0;
          const float s0 = part == 0 ? QS : (part == 1 && !mu0 ? 0x1p-22f : 1.f), s1 = part == 0 ? QS : (part == 1 && !mu1 ? 0x1p-22f : 1.f);
          const float a0 = c0.x * s0, b0 = c0.y * s0, a1 = c1.x * s1, b1 = c1.y * s1;
          float nA0 = 0.f, nA1 = 0.f, nB0 = 0.f, nB1 = 0.f;
#pragma unroll
          for (int m = 0; m < 5; m++) {
            const int b = pr * 5 + m;
            const float2 cc = *(const float2*)(cs + b * 8 + q * 2);
            uint8_t* ptr = stg + off[m] + mt * 3072;
            const float v0 = fmaf(a0, acc[mt][4 * b], b0 * cc.x), v1 = fmaf(a0, acc[mt][4 * b + 1], b0 * cc.y);
            const float v2 = fmaf(a1, acc[mt][4 * b + 2], b1 * cc.x), v3 = fmaf(a1, acc[mt][4 * b + 3], b1 * cc.y);
            *(uint32_t*)ptr = pack_bf16(v0, v1);
            *(uint32_t*)(ptr + 384) = pack_bf16(v2, v3);
            const float n0 = fmaf(v0, v0, v1 * v1), n1 = fmaf(v2, v2, v3 * v3);
            if (m < 2) { nA0 += n0; nA1 += n1; } else if (m > 2) { nB0 += n0; nB1 += n1; }
            else if (q < 2) { nA0 += n0; nA1 += n1; } else { nB0 += n0; nB1 += n1; }
          }
          const uint2 ex = part == 0 ? make_uint2(0x3F803F80u, 0x00003F80u)
                                     : (part == 1 ? (mu ? make_uint2(0u, 0u) : make_uint2(0x377C3C00u, 0x00003020u)) : make_uint2(0x00003F80u, 0u));
          *(uint2*)(stg + mt * 3072 + (q >> 1) * 6144 + (q & 1) * 384 + 264) = ex;
          float x = (q & 1) ? nA1 : nA0, y = (q & 1) ? nB1 : nB0;
          x += __shfl_xor_sync(0xffffffffu, (q & 1) ? nA0 : nA1, 1);
          y += __shfl_xor_sync(0xffffffffu, (q & 1) ? nB0 : nB1, 1);
          float n = (q & 2) ? y : x;
          n += __shfl_xor_sync(0xffffffffu, (q & 2) ? x : y, 2);
          nrm[mt] = (part == 1 && !mu) ? n * 0x1p44f : n;
        }
        asm volatile("fence.proxy.async.shared::cta;" ::: "memory");
        named_bar(2 + wg, 128);
        if ((tid & 127) < 2) bulk_s2g((uint8_t*)g_qkv + (size_t)(c * 6 + pr * 2 + lane) * HEAD_BYTES + rbk * 6144, sbase + soff + lane * 6144, 6144);
        if (part < 2) atomicMax(smax + pr * 2 + (q >> 1), max(__float_as_uint(nrm[0]) & 0x7FFFFFFFu, __float_as_uint(nrm[1]) & 0x7FFFFFFFu));
      }
      named_bar(2 + wg, 128);
      if ((tid & 127) < 6 && c * 6 + (tid & 127) < 64) atomicMax(fl + NORM_OFF + c * 6 + (tid & 127), smax[tid & 127]);
      if ((tid & 127) < 2) {
        asm volatile("cp.async.bulk.wait_group 0;" ::: "memory");
      }
    }
  }
}

__device__ __forceinline__ uint32_t exp2_poly_pair(float a0, float a1) {
  const uint32_t v = __byte_perm(__float_as_uint(a0), __float_as_uint(a1), 0x7430);
  const uint32_t e = __byte_perm(__float_as_uint(a0), __float_as_uint(a1), 0x6521);
  uint32_t u;
  asm("fma.rn.f16x2 %0, %1, %2, %3;" : "=r"(u) : "r"(v), "r"(0x1d611d61u), "r"(0xa012a012u));
  asm("fma.rn.f16x2 %0, %1, %2, %3;" : "=r"(u) : "r"(u), "r"(v), "r"(0x21622162u));
  uint32_t r;
  asm("{\n.reg .b32 t;\nshl.b32 t, %1, 7;\nadd.u32 %0, t, %2;\n}" : "=r"(r) : "r"(e), "r"(u));
  return r;
}
constexpr int KPITCH = 6144 + 128;
constexpr int ATT_V = 16 * KPITCH, ATT_JOB = ATT_V + HEAD_BYTES, ATT_BAR = ATT_JOB + 2 * 15360, ATT_SMEM = ATT_BAR + 128;

__device__ __forceinline__ void att_store(const float (&O)[12], int row0, int h, int lane) {
  const float l0 = __shfl_sync(0xffffffffu, O[8], (lane & ~3) | 2), l1 = __shfl_sync(0xffffffffu, O[10], (lane & ~3) | 2);
  const float r0 = __fdividef(1.f, l0), r1 = __fdividef(1.f, l1);
#pragma unroll
  for (int c = 0; c < 3; c++)
    if (c < 2 || (lane & 3) < 2) {
      const int col = h * 20 + c * 8 + (lane & 3) * 2;
      uint32_t* o0 = (uint32_t*)g_o + o_line(row0, col >> 3) * 32 + (row0 & 7) * 4 + ((col & 7) >> 1);
      o0[0] = pack_bf16(O[4 * c] * r0, O[4 * c + 1] * r0);
      o0[256] = pack_bf16(O[4 * c + 2] * r1, O[4 * c + 3] * r1);
    }
}

struct alignas(64) AttParams {
  CUtensorMap b_w2;
  const unsigned int* norms;
  unsigned int *reset_a, *reset_b, *reset_c;
  const uint32_t* zeros;
  int jobs;
};
__global__ void __launch_bounds__(512, 1) att_kernel(const __grid_constant__ AttParams p) {
  const unsigned int* norms = p.norms;
  extern __shared__ __align__(1024) uint8_t smem[];
  const uint32_t sK = smem_u32(smem), sV = sK + ATT_V, bars = sK + ATT_BAR;
  const int h = blockIdx.x >> 2, qt = blockIdx.x & 3;
  const int tid = threadIdx.x, lane = tid & 31, wg = __shfl_sync(0xffffffffu, tid >> 7, 0), warp = (tid >> 5) & 3;
  if (tid == 0) {
    for (int c = 0; c < 9; c++) mbar_init(bars + c * 8, 1);
    asm volatile("fence.mbarrier_init.release.cluster;" ::: "memory");
  }
  *(uint32_t*)(smem + (tid >> 5) * KPITCH + 6144 + lane * 4) = 0u;
  asm volatile("fence.proxy.async;" ::: "memory");
  const uint32_t z0 = __ldg(p.zeros + (tid & 1)), z1 = __ldg(p.zeros + 2 + (tid & 1));
  __syncthreads();
  pdl_wait();
  pdl_launch();
  const uint8_t* gq = (const uint8_t*)g_qkv + (size_t)h * HEAD_BYTES;
  const uint64_t dK = mk_desc(sK, 128, 384, 0);
  const uint64_t dV = mk_desc(sV, 384, 128, 0);
  uint32_t q[6];
  auto load_q = [&](int row0) {
    const uint32_t* qa = (const uint32_t*)(gq + (row0 >> 3) * 384 + (row0 & 7) * 16) + (lane & 3);
    q[0] = __ldcg(qa); q[1] = __ldcg(qa + 96); q[2] = __ldcg(qa + 32); q[3] = __ldcg(qa + 128); q[4] = __ldcg(qa + 64); q[5] = __ldcg(qa + 160);
  };
  const int rowA = qt * 512 + wg * 64 + warp * 16 + (lane >> 2);
  load_q(rowA);
  auto load_kv = [&](int c) {
    mbar_expect_tx(bars + c * 8, 24576);
    bulk_g2s(sK + c * 2 * KPITCH, gq + 32 * HEAD_BYTES + c * 12288, 6144, bars + c * 8);
    bulk_g2s(sK + (c * 2 + 1) * KPITCH, gq + 32 * HEAD_BYTES + c * 12288 + 6144, 6144, bars + c * 8);
    bulk_g2s(sV + c * 12288, gq + 64 * HEAD_BYTES + c * 12288, 12288, bars + c * 8);
  };
  if (tid == 480) { load_kv(0); load_kv(1); }
  __syncwarp();
  auto load_rest = [&]() {
        if (tid == 480) {
#pragma unroll 1
          for (int c = 2; c < 8; c++) load_kv(c);
          if (p.jobs) {
            mbar_expect_tx(bars + 64, blockIdx.x < 16 ? 30720 : 15360);
#pragma unroll 1
            for (int job = blockIdx.x; job < 144; job += 128)
#pragma unroll 1
              for (int b = 0; b < 5; b++) tma_3d(sK + ATT_JOB + (job >> 7) * 15360 + b * 3072, &p.b_w2, b * 16, job / 18, (job % 18) * 96, bars + 64);
          }
        }
        __syncwarp();
  };
  const bool unsafe = !(__uint_as_float(__ldcg(norms + h)) * __uint_as_float(__ldcg(norms + 32 + h)) <= 3500.f);
  if (blockIdx.x == 0 && tid < NORM_OFF) { p.reset_a[tid] = 0u; if (tid < FLAG_SET - NORM_OFF) p.reset_b[tid] = 0u; if (p.reset_c) p.reset_c[tid] = 0u; }
  auto fast_tile = [&](auto first, int row0) -> bool {
      constexpr int tt = first.value ? 0 : 1;
      float S[64], O[12];
      uint32_t P[32];
#pragma unroll
      for (int k = 0; k < 64; k++) S[k] = 0.f;
#pragma unroll
      for (int k = 0; k < 12; k++) O[k] = 0.f;
      auto blocks = [&](int g0, int g1) {
        uint64_t gk = dK + g0 * (KPITCH / 16), gv = dV + g0 * 384;
#pragma unroll 1
        for (int g = g0; g < g1; g++) {
        if (tt == 0 && (g & 1) == 0) mbar_wait_warp(bars + (g >> 1) * 8, 0);
        wg_fence();
        wgmma_rs_n128<0>(S, q[0], q[1], q[2], q[3], gk, 0);
        wgmma_rs_n128<0>(S, q[4], q[5], z0, z1, gk + 16, 1);
        wg_commit();
        wg_wait<0>();
        fence_regs(S);
#pragma unroll
        for (int hf = 0; hf < 8; hf++) {
          constexpr int NB = 16 / 8;
          uint32_t (&Ph)[2 * NB] = *(uint32_t(*)[2 * NB])(P + hf * 2 * NB);
#pragma unroll
          for (int b = hf * NB; b < hf * NB + NB; b++) {
            if (is_mufu(b)) { P[2 * b] = pack_bf16(ex2(S[4 * b]), ex2(S[4 * b + 1])); P[2 * b + 1] = pack_bf16(ex2(S[4 * b + 2]), ex2(S[4 * b + 3])); }
            else { P[2 * b] = exp2_poly_pair(S[4 * b], S[4 * b + 1]); P[2 * b + 1] = exp2_poly_pair(S[4 * b + 2], S[4 * b + 3]); }
          }
          fence_regs(Ph);
          wg_fence();
#pragma unroll
          for (int s = hf * NB / 2; s < (hf + 1) * NB / 2; s++) wgmma_rs_n24<1>(O, P[4 * s], P[4 * s + 1], P[4 * s + 2], P[4 * s + 3], gv + s * 48, 1);
          wg_commit();
        }
        wg_wait<0>();
        gk += KPITCH / 16; gv += 384;
        }
      };
      if (tt == 0) {
        blocks(0, 2);
        load_rest();
        blocks(2, 16);
      } else blocks(0, 16);
      fence_regs(O);
      att_store(O, row0, h, lane);
      bool bad = false;
      float m = 0.f;
#pragma unroll
      for (int k = 0; k < 12; k++) { m = fmaxf(m, fabsf(O[k])); bad |= (O[k] != O[k]); }
      bad |= !(m <= 3e38f);
      if ((lane & 3) == 2) bad |= !(O[8] >= 0x1p-20f) || !(O[10] >= 0x1p-20f);
      uint32_t r;
      asm volatile("{\n.reg .pred p, r;\nsetp.ne.u32 p, %1, 0;\nbarrier.red.or.pred.aligned r, %2, 128, p;\nselp.u32 %0, 1, 0, r;\n}\n" : "=r"(r) : "r"((uint32_t)bad), "r"(1 + wg) : "memory");
      return r != 0;
  };
  auto safe_tile = [&](int row0) {
      float S[64], O[12];
      uint32_t P[32];
#pragma unroll
      for (int k = 0; k < 64; k++) S[k] = 0.f;
      if ((lane & 3) >= 2) { q[4] = 0u; q[5] = 0u; }
      float m0 = -INFINITY, m1 = -INFINITY;
#pragma unroll
      for (int k = 0; k < 12; k++) O[k] = 0.f;
      uint64_t gk = dK, gv = dV;
#pragma unroll 1
      for (int g = 0; g < 16; g++) {
        wg_fence();
        wgmma_rs_n128<0>(S, q[0], q[1], q[2], q[3], gk, 0);
        wgmma_rs_n128<0>(S, q[4], q[5], z0, z1, gk + 16, 1);
        wg_commit();
        wg_wait<0>();
        fence_regs(S);
        float x0 = m0, x1 = m1;
#pragma unroll
        for (int b = 0; b < 16; b++) {
          if (!is_mufu(b)) { S[4 * b] *= 0x1p22f; S[4 * b + 1] *= 0x1p22f; S[4 * b + 2] *= 0x1p22f; S[4 * b + 3] *= 0x1p22f; }
          x0 = fmaxf(x0, fmaxf(S[4 * b], S[4 * b + 1]));
          x1 = fmaxf(x1, fmaxf(S[4 * b + 2], S[4 * b + 3]));
        }
        x0 = fmaxf(x0, __shfl_xor_sync(0xffffffffu, x0, 1)); x1 = fmaxf(x1, __shfl_xor_sync(0xffffffffu, x1, 1));
        x0 = fmaxf(x0, __shfl_xor_sync(0xffffffffu, x0, 2)); x1 = fmaxf(x1, __shfl_xor_sync(0xffffffffu, x1, 2));
        const float al0 = ex2(m0 - x0), al1 = ex2(m1 - x1);
        m0 = x0; m1 = x1;
#pragma unroll
        for (int c = 0; c < 3; c++) { O[4 * c] *= al0; O[4 * c + 1] *= al0; O[4 * c + 2] *= al1; O[4 * c + 3] *= al1; }
#pragma unroll
        for (int b = 0; b < 16; b++) {
          P[2 * b] = pack_bf16(ex2(S[4 * b] - m0), ex2(S[4 * b + 1] - m0));
          P[2 * b + 1] = pack_bf16(ex2(S[4 * b + 2] - m1), ex2(S[4 * b + 3] - m1));
        }
        fence_regs(P);
        fence_regs(O);
        wg_fence();
#pragma unroll
        for (int s = 0; s < 8; s++) wgmma_rs_n24<1>(O, P[4 * s], P[4 * s + 1], P[4 * s + 2], P[4 * s + 3], gv + s * 48, 1);
        wg_commit();
        wg_wait<0>();
        fence_regs(O);
        gk += KPITCH / 16; gv += 384;
      }
      att_store(O, row0, h, lane);
      named_bar(1 + wg, 128);
  };
  bool redo = true;
  if (!__any_sync(0xffffffffu, unsafe)) redo = fast_tile(IC<1>{}, rowA);
  else {
    load_rest();
#pragma unroll 1
    for (int c = 0; c < 8; c++) mbar_wait(bars + c * 8, 0);
  }
  if (__any_sync(0xffffffffu, redo)) safe_tile(rowA);
  load_q(rowA + 256);
  if (tid == 480 && p.jobs) {
    mbar_wait(bars + 64, 0);
#pragma unroll 1
    for (int job = blockIdx.x; job < 144; job += 128) bulk_s2g(g_wt + WT_W2 + job * 15360, sK + ATT_JOB + (job >> 7) * 15360, 15360);
  }
  __syncwarp();
  redo = true;
  if (!__any_sync(0xffffffffu, unsafe)) redo = fast_tile(IC<0>{}, rowA + 256);
  if (__any_sync(0xffffffffu, redo)) safe_tile(rowA + 256);
  if (tid == 480) asm volatile("cp.async.bulk.wait_group 0;" ::: "memory");
}

typedef CUresult (*EncodeFn)(CUtensorMap*, CUtensorMapDataType, cuuint32_t, void*, const cuuint64_t*, const cuuint64_t*, const cuuint32_t*,
                             const cuuint32_t*, CUtensorMapInterleave, CUtensorMapSwizzle, CUtensorMapL2promotion, CUtensorMapFloatOOBfill);

static void make_a(EncodeFn enc, CUtensorMap* m, const void* ptr, int K) {
  cuuint64_t dims[2] = {(cuuint64_t)K, (cuuint64_t)SEQ}, strides[1] = {(cuuint64_t)K * 2};
  cuuint32_t box[2] = {64, 128}, es[2] = {1, 1};
  enc(m, CU_TENSOR_MAP_DATA_TYPE_BFLOAT16, 2, (void*)ptr, dims, strides, box, es, CU_TENSOR_MAP_INTERLEAVE_NONE, CU_TENSOR_MAP_SWIZZLE_128B,
      CU_TENSOR_MAP_L2_PROMOTION_NONE, CU_TENSOR_MAP_FLOAT_OOB_FILL_NONE);
}
static void make_out(EncodeFn enc, CUtensorMap* m, void* ptr) {
  cuuint64_t dims[2] = {(cuuint64_t)DM, (cuuint64_t)SEQ}, strides[1] = {(cuuint64_t)DM * 2};
  cuuint32_t box[2] = {80, 64}, es[2] = {1, 1};
  enc(m, CU_TENSOR_MAP_DATA_TYPE_BFLOAT16, 2, ptr, dims, strides, box, es, CU_TENSOR_MAP_INTERLEAVE_NONE, CU_TENSOR_MAP_SWIZZLE_NONE,
      CU_TENSOR_MAP_L2_PROMOTION_NONE, CU_TENSOR_MAP_FLOAT_OOB_FILL_NONE);
}
static void make_b(EncodeFn enc, CUtensorMap* m, const void* ptr, int K, int N, int BN, int bk, int bw) {
  cuuint64_t dims[3] = {(cuuint64_t)BN, (cuuint64_t)(N / BN), (cuuint64_t)K}, strides[2] = {(cuuint64_t)BN * 2, (cuuint64_t)N * 2};
  cuuint32_t box[3] = {(cuuint32_t)bw, 1, (cuuint32_t)bk}, es[3] = {1, 1, 1};
  enc(m, CU_TENSOR_MAP_DATA_TYPE_BFLOAT16, 3, (void*)ptr, dims, strides, box, es, CU_TENSOR_MAP_INTERLEAVE_NONE, bw == 64 ? CU_TENSOR_MAP_SWIZZLE_128B : CU_TENSOR_MAP_SWIZZLE_32B,
      CU_TENSOR_MAP_L2_PROMOTION_NONE, CU_TENSOR_MAP_FLOAT_OOB_FILL_NONE);
}
template <typename... KArgs, typename... Args>
static void launch(void (*kern)(KArgs...), int grid, int threads, int smem, bool pdl, Args... args) {
  cudaFuncSetAttribute(kern, cudaFuncAttributeMaxDynamicSharedMemorySize, smem);
  cudaLaunchConfig_t cfg = {};
  cfg.gridDim = dim3(grid); cfg.blockDim = dim3(threads); cfg.dynamicSmemBytes = smem; cfg.stream = cudaStreamPerThread;
  cudaLaunchAttribute at[1];
  at[0].id = cudaLaunchAttributeProgrammaticStreamSerialization; at[0].val.programmaticStreamSerializationAllowed = 1;
  cfg.attrs = at; cfg.numAttrs = pdl ? 1 : 0;
  cudaLaunchKernelEx(&cfg, kern, KArgs(args)...);
}

static void make_pref(signed char* pref, int ntpc) {
  auto kern = chain_kernel<PH_WO | PH_W1 | PH_W2, false, true>;
  cudaFuncSetAttribute(kern, cudaFuncAttributeMaxDynamicSharedMemorySize, CHAIN_SMEM);
  cudaFuncSetAttribute(kern, cudaFuncAttributeNonPortableClusterSizeAllowed, 1);
  int n[10] = {0};
  for (int t = 2; t <= 8; t++) {
    cudaLaunchConfig_t cfg = {};
    cfg.gridDim = dim3(2 * t * 16); cfg.blockDim = dim3(CHAIN_THREADS); cfg.dynamicSmemBytes = CHAIN_SMEM;
    cudaLaunchAttribute at[1];
    at[0].id = cudaLaunchAttributeClusterDimension; at[0].val.clusterDim.x = 2 * t; at[0].val.clusterDim.y = 1; at[0].val.clusterDim.z = 1;
    cfg.attrs = at; cfg.numAttrs = 1;
    if (cudaOccupancyMaxActiveClusters(&n[t], kern, &cfg) != cudaSuccess) { n[t] = -1; cudaGetLastError(); }
  }
  int best[10] = {0}, cnt[10], found = 0;
  for (int code = 0; code < 1000000 && !found; code++) {
    int c = code, tot = 0, g = 0;
    for (int m = 0; m < 10; m++) cnt[m] = 0;
    for (int m = 4; m <= 9; m++) { cnt[m] = c % 10; c /= 10; tot += cnt[m] * m; g += cnt[m]; }
    if (g > 9 || tot > ntpc) continue;
    bool ok = true;
    for (int t = 3; t <= 8 && ok; t++) { int s = 0; for (int m = 4; m <= 9; m++) s += cnt[m] * (m / t); ok = (s == n[t]); }
    if (ok) { found = 1; for (int m = 0; m < 10; m++) best[m] = cnt[m]; }
  }
  int grp[80], size[10], ng = 0, id = 0;
  for (int t = 0; t < 80; t++) { grp[t] = -1; pref[2 * t] = pref[2 * t + 1] = -1; }
  if (found) {
    for (int m = 4; m <= 9; m++) for (int k = 0; k < best[m]; k++) size[ng++] = m;
    for (int r = 0; r < 9; r++) for (int g = 0; g < ng; g++) if (size[g] > r && id < ntpc) grp[id++] = g;
  }
  int nb = 0;
  bool used[80] = {false};
  auto put = [&](int t, int blk, int w) {
    const int tile = blk * 16 + w * 2;
    pref[2 * t] = (signed char)tile; pref[2 * t + 1] = (signed char)(tile + 1); used[t] = true;
  };
  for (int g = 0; g < ng && nb < 8; g++)
    if (size[g] >= 8) {
      int w = 0;
      for (int t = 0; t < ntpc && w < 8; t++) if (grp[t] == g) put(t, nb, w++);
      nb++;
    }
  int pos = nb * 8;
  for (int pass = 0; pass < 2; pass++)
    for (int g = 0; g <= ng; g++)
      for (int t = 0; t < ntpc && pos < 64; t++)
        if (!used[t] && (g < ng ? (grp[t] == g && (size[g] < 8) == (pass == 0)) : (pass == 1 && grp[t] < 0))) { put(t, pos >> 3, pos & 7); pos++; }
}

extern "C" void kernel_launch(void* const* d_in, const int* in_sizes, int n_in, void* d_out, int out_size) {
  const bf16* x = (const bf16*)d_in[0];
  const bf16* wqkv = (const bf16*)d_in[1];
  const bf16* wo = (const bf16*)d_in[2];
  const bf16* w1 = (const bf16*)d_in[4];
  const bf16* b1 = (const bf16*)d_in[5];
  const bf16* w2 = (const bf16*)d_in[6];
  const bf16* b2 = (const bf16*)d_in[7];
  void* fn = nullptr;
  cudaDriverEntryPointQueryResult qr;
  cudaGetDriverEntryPoint("cuTensorMapEncodeTiled", &fn, cudaEnableDefault, &qr);
  EncodeFn enc = (EncodeFn)fn;
  void *px0, *px2, *pf, *pz;
  cudaGetSymbolAddress(&px0, g_x0);
  cudaGetSymbolAddress(&px2, g_x2); cudaGetSymbolAddress(&pf, g_s);
  unsigned int* flags = ((Small*)pf)->flags;
  pz = ((Small*)pf)->zeros;

  int nsm = 132;
  cudaDeviceGetAttribute(&nsm, cudaDevAttrMultiProcessorCount, 0);
  const int ngrid = nsm >= 128 ? (nsm > 160 ? 160 : (nsm & ~1)) : 128;
  ChainParams p;
  make_pref(p.pref, ngrid / 2);
  make_a(enc, &p.a_x, x, DM);
  make_out(enc, &p.o_out, d_out);
  AttParams ap;
  make_b(enc, &p.b_wo, wo, DM, DM, 80, 64, 16); make_b(enc, &p.b_w1, w1, DM, FF, 216, 64, 16); make_b(enc, &ap.b_w2, w2, FF, DM, 80, 96, 16);
  ap.zeros = (const uint32_t*)pz;
  make_b(enc, &p.b_wqkv, wqkv, DM, 1920, 120, 64, 64);
  p.xres = (const bf16*)px0; p.xin = x; p.b1 = b1; p.b2 = b2; p.flags = flags;

  launch(chain_kernel<PH_QKV, true, false>, ngrid, CHAIN_THREADS, CHAIN_SMEM, false, p);
  ap.norms = flags + NORM_OFF; ap.reset_a = flags; ap.reset_b = flags + FLAG_SET + NORM_OFF; ap.reset_c = flags + 2 * FLAG_SET; ap.jobs = 1;
  launch(att_kernel, 128, 512, ATT_SMEM, true, ap);
  p.flags = flags + FLAG_SET;
  launch(chain_kernel<PH_WO | PH_W1 | PH_W2 | PH_QKV, false, false>, ngrid, CHAIN_THREADS, CHAIN_SMEM, true, p);
  ap.norms = flags + FLAG_SET + NORM_OFF; ap.reset_a = flags + FLAG_SET; ap.reset_b = flags + NORM_OFF; ap.reset_c = nullptr; ap.jobs = 0;
  launch(att_kernel, 128, 512, ATT_SMEM, true, ap);
  p.xres = (const bf16*)px2; p.flags = flags + 2 * FLAG_SET;
  launch(chain_kernel<PH_WO | PH_W1 | PH_W2, false, true>, ngrid, CHAIN_THREADS, CHAIN_SMEM, true, p);
}
```

```cpp
#include <cuda_runtime.h>
#include <cuda_bf16.h>
#include <cuda.h>
#include <stdint.h>

typedef __nv_bfloat16 bf16;

constexpr int SEQ = 2048, DM = 640, FF = 1728;
constexpr float LN_EPS = 1e-5f;
constexpr int HEAD_BYTES = 98304;
constexpr uint32_t MUFU_MASK = 0x4949u;
__host__ __device__ constexpr bool is_mufu(int g) { return (MUFU_MASK >> (g & 15)) & 1u; }

__device__ __align__(1024) bf16 g_qkv[96 * (HEAD_BYTES / 2)];
constexpr int WT_WO = 0, WT_W1 = WT_WO + 80 * 10240, WT_W2 = WT_W1 + 160 * 14336, WT_QKV = WT_W2 + 144 * 15360, WT_END = WT_QKV + 160 * 16384;
__device__ __align__(1024) uint8_t g_wt[WT_END];
__device__ __forceinline__ int x_line(int row, int cg) { return (((row >> 7) * 10 + (cg >> 3)) * 16 + ((row >> 3) & 15)) * 8 + (cg & 7); }
__device__ __forceinline__ int o_line(int row, int cg) { return (((row >> 6) * 10 + (cg >> 3)) * 8 + ((row >> 3) & 7)) * 8 + (cg & 7); }
__device__ __forceinline__ int h_line(int row, int cg) { return (((row >> 6) * 18 + cg / 12) * 8 + ((row >> 3) & 7)) * 12 + cg % 12; }
__device__ __align__(1024) bf16 g_x0[SEQ * DM];
__device__ __align__(1024) bf16 g_o[SEQ * DM];
__device__ __align__(1024) bf16 g_x1[SEQ * DM];
__device__ __align__(1024) bf16 g_x2[SEQ * DM];
__device__ __align__(1024) bf16 g_h[SEQ * FF];
constexpr int FLAG_SET = 320, NORM_OFF = 256;
struct Small {
  float2 st0[2 * SEQ];
  float2 st1[8 * SEQ];
  float2 st2[8 * SEQ];
  float csp_w1[10 * 1792];
  float cs_qkv[1920];
  unsigned int flags[3 * FLAG_SET];
  uint32_t zeros[4];
};
__device__ __align__(1024) Small g_s;

__device__ __forceinline__ uint32_t smem_u32(const void* p) { return (uint32_t)__cvta_generic_to_shared(p); }
__device__ __forceinline__ void mbar_init(uint32_t bar, int cnt) { asm volatile("mbarrier.init.shared::cta.b64 [%0], %1;" ::"r"(bar), "r"(cnt) : "memory"); }
__device__ __forceinline__ void mbar_expect_tx(uint32_t bar, uint32_t bytes) { asm volatile("mbarrier.arrive.expect_tx.shared::cta.b64 _, [%0], %1;" ::"r"(bar), "r"(bytes) : "memory"); }
__device__ __forceinline__ void mbar_arrive(uint32_t bar) { asm volatile("mbarrier.arrive.shared::cta.b64 _, [%0];" ::"r"(bar) : "memory"); }
__device__ __forceinline__ void mbar_arrive_if(uint32_t bar, bool c) {
  asm volatile("{\n.reg .pred p;\nsetp.ne.u32 p, %1, 0;\n@p mbarrier.arrive.shared::cta.b64 _, [%0];\n}\n" ::"r"(bar), "r"((uint32_t)c) : "memory");
}
__device__ __forceinline__ bool mbar_try(uint32_t bar, uint32_t parity) {
  uint32_t ok;
  asm volatile("{\n.reg .pred p;\nmbarrier.try_wait.parity.shared::cta.b64 p, [%1], %2;\nselp.u32 %0, 1, 0, p;\n}\n" : "=r"(ok) : "r"(bar), "r"(parity) : "memory");
  return ok != 0;
}
__device__ __forceinline__ bool mbar_test(uint32_t bar, uint32_t parity) {
  uint32_t ok;
  asm volatile("{\n.reg .pred p;\nmbarrier.test_wait.parity.shared::cta.b64 p, [%1], %2;\nselp.u32 %0, 1, 0, p;\n}\n" : "=r"(ok) : "r"(bar), "r"(parity) : "memory");
  return ok != 0;
}
__device__ __forceinline__ void mbar_wait(uint32_t bar, uint32_t parity) {
  if (mbar_try(bar, parity)) return;
#pragma unroll 1
  for (int it = 0; it < (1 << 22); it++)
    if (mbar_try(bar, parity)) return;
  __trap();
}
__device__ __forceinline__ void mbar_wait_warp(uint32_t bar, uint32_t parity) {
#pragma unroll 1
  for (int it = 0; !__all_sync(0xffffffffu, mbar_try(bar, parity)); it++)
    if (it > (1 << 22)) __trap();
}
__device__ __forceinline__ void flag_wait(const unsigned int* f, unsigned int target) {
  unsigned int v;
#pragma unroll 1
  for (int it = 0; it < (1 << 22); it++) {
    asm volatile("ld.acquire.gpu.global.u32 %0, [%1];" : "=r"(v) : "l"(f) : "memory");
    if (v >= target) return;
  }
  __trap();
}
__device__ __forceinline__ void flag_signal(unsigned int* f) { asm volatile("red.release.gpu.global.add.u32 [%0], 1;" ::"l"(f) : "memory"); }
__device__ __forceinline__ void fence_async_global() { asm volatile("fence.proxy.async.global;" ::: "memory"); }
__device__ __forceinline__ void pdl_wait() { asm volatile("griddepcontrol.wait;" ::: "memory"); }
__device__ __forceinline__ void pdl_launch() { asm volatile("griddepcontrol.launch_dependents;" ::: "memory"); }
__device__ __forceinline__ void named_bar(int id, int n) { asm volatile("bar.sync %0, %1;" ::"r"(id), "r"(n) : "memory"); }
__device__ __forceinline__ void bulk_g2s(uint32_t dst, const void* src, uint32_t bytes, uint32_t bar) {
  asm volatile("cp.async.bulk.shared::cluster.global.mbarrier::complete_tx::bytes [%0], [%1], %2, [%3];" ::"r"(dst), "l"(src), "r"(bytes), "r"(bar) : "memory");
}
__device__ __forceinline__ void tma_2d(uint32_t dst, const CUtensorMap* m, int c0, int c1, uint32_t bar) {
  asm volatile("cp.async.bulk.tensor.2d.shared::cluster.global.mbarrier::complete_tx::bytes [%0], [%1, {%3, %4}], [%2];" ::"r"(dst), "l"(m), "r"(bar), "r"(c0), "r"(c1) : "memory");
}
__device__ __forceinline__ void tma_3d(uint32_t dst, const CUtensorMap* m, int c0, int c1, int c2, uint32_t bar) {
  asm volatile("cp.async.bulk.tensor.3d.shared::cluster.global.mbarrier::complete_tx::bytes [%0], [%1, {%3, %4, %5}], [%2];" ::"r"(dst), "l"(m), "r"(bar), "r"(c0), "r"(c1), "r"(c2) : "memory");
}
__device__ __forceinline__ void prefetch_map(const CUtensorMap* m) { asm volatile("prefetch.tensormap [%0];" ::"l"(m) : "memory"); }
__device__ __forceinline__ void wg_fence() { asm volatile("wgmma.fence.sync.aligned;" ::: "memory"); }
__device__ __forceinline__ void wg_commit() { asm volatile("wgmma.commit_group.sync.aligned;" ::: "memory"); }
template <int N> __device__ __forceinline__ void wg_wait() { asm volatile("wgmma.wait_group.sync.aligned %0;" ::"n"(N) : "memory"); }
template <int N> __device__ __forceinline__ void fence_regs(float (&d)[N]) {
#pragma unroll
  for (int i = 0; i < N; i++) asm volatile("" : "+f"(d[i])::"memory");
}
template <int N> __device__ __forceinline__ void fence_regs(uint32_t (&d)[N]) {
#pragma unroll
  for (int i = 0; i < N; i++) asm volatile("" : "+r"(d[i])::"memory");
}
__device__ __forceinline__ uint64_t mk_desc(uint32_t addr, uint32_t lbo, uint32_t sbo, uint64_t swz) {
  return (uint64_t)((addr & 0x3FFFF) >> 4) | ((uint64_t)(lbo >> 4) << 16) | ((uint64_t)(sbo >> 4) << 32) | (swz << 62);
}
__device__ __forceinline__ uint32_t pack_bf16(float lo, float hi) {
  uint32_t r;
  asm("cvt.rn.bf16x2.f32 %0, %1, %2;" : "=r"(r) : "f"(hi), "f"(lo));
  return r;
}
__device__ __forceinline__ float bf_lo(uint32_t v) { return __uint_as_float(v << 16); }
__device__ __forceinline__ float bf_hi(uint32_t v) { return __uint_as_float(v & 0xFFFF0000u); }
__device__ __forceinline__ float ex2(float x) { float r; asm("ex2.approx.ftz.f32 %0, %1;" : "=f"(r) : "f"(x)); return r; }

template<int TB> __device__ __forceinline__ void wgmma_rs_n24(float (&d)[12], uint32_t a0, uint32_t a1, uint32_t a2, uint32_t a3, uint64_t db, int sd) {
  asm volatile("{\n.reg .pred p;\nsetp.ne.b32 p, %17, 0;\n"
    "wgmma.mma_async.sync.aligned.m64n24k16.f32.bf16.bf16 "
    "{%0,%1,%2,%3,%4,%5,%6,%7,%8,%9,%10,%11}, "
    "{%12,%13,%14,%15}, %16, p, 1, 1, %18;\n}\n"
    : "+f"(d[0]),"+f"(d[1]),"+f"(d[2]),"+f"(d[3]),"+f"(d[4]),"+f"(d[5]),"+f"(d[6]),"+f"(d[7]),"+f"(d[8]),"+f"(d[9]),"+f"(d[10]),"+f"(d[11])
    : "r"(a0), "r"(a1), "r"(a2), "r"(a3), "l"(db), "r"(sd), "n"(TB));
}
template<int TB> __device__ __forceinline__ void wgmma_rs_n120(float (&d)[60], uint32_t a0, uint32_t a1, uint32_t a2, uint32_t a3, uint64_t db, int sd) {
  asm volatile("{\n.reg .pred p;\nsetp.ne.b32 p, %65, 0;\n"
    "wgmma.mma_async.sync.aligned.m64n120k16.f32.bf16.bf16 "
    "{%0,%1,%2,%3,%4,%5,%6,%7,%8,%9,%10,%11,%12,%13,%14,%15,%16,%17,%18,%19,%20,%21,%22,%23,%24,%25,%26,%27,%28,%29,%30,%31,%32,%33,%34,%35,%36,%37,%38,%39,%40,%41,%42,%43,%44,%45,%46,%47,%48,%49,%50,%51,%52,%53,%54,%55,%56,%57,%58,%59}, "
    "{%60,%61,%62,%63}, %64, p, 1, 1, %66;\n}\n"
    : "+f"(d[0]),"+f"(d[1]),"+f"(d[2]),"+f"(d[3]),"+f"(d[4]),"+f"(d[5]),"+f"(d[6]),"+f"(d[7]),"+f"(d[8]),"+f"(d[9]),"+f"(d[10]),"+f"(d[11]),"+f"(d[12]),"+f"(d[13]),"+f"(d[14]),"+f"(d[15]),"+f"(d[16]),"+f"(d[17]),"+f"(d[18]),"+f"(d[19]),"+f"(d[20]),"+f"(d[21]),"+f"(d[22]),"+f"(d[23]),"+f"(d[24]),"+f"(d[25]),"+f"(d[26]),"+f"(d[27]),"+f"(d[28]),"+f"(d[29]),"+f"(d[30]),"+f"(d[31]),"+f"(d[32]),"+f"(d[33]),"+f"(d[34]),"+f"(d[35]),"+f"(d[36]),"+f"(d[37]),"+f"(d[38]),"+f"(d[39]),"+f"(d[40]),"+f"(d[41]),"+f"(d[42]),"+f"(d[43]),"+f"(d[44]),"+f"(d[45]),"+f"(d[46]),"+f"(d[47]),"+f"(d[48]),"+f"(d[49]),"+f"(d[50]),"+f"(d[51]),"+f"(d[52]),"+f"(d[53]),"+f"(d[54]),"+f"(d[55]),"+f"(d[56]),"+f"(d[57]),"+f"(d[58]),"+f"(d[59])
    : "r"(a0), "r"(a1), "r"(a2), "r"(a3), "l"(db), "r"(sd), "n"(TB));
}
template<int TB> __device__ __forceinline__ void wgmma_rs_n128(float (&d)[64], uint32_t a0, uint32_t a1, uint32_t a2, uint32_t a3, uint64_t db, int sd) {
  asm volatile("{\n.reg .pred p;\nsetp.ne.b32 p, %69, 0;\n"
    "wgmma.mma_async.sync.aligned.m64n128k16.f32.bf16.bf16 "
    "{%0,%1,%2,%3,%4,%5,%6,%7,%8,%9,%10,%11,%12,%13,%14,%15,%16,%17,%18,%19,%20,%21,%22,%23,%24,%25,%26,%27,%28,%29,%30,%31,%32,%33,%34,%35,%36,%37,%38,%39,%40,%41,%42,%43,%44,%45,%46,%47,%48,%49,%50,%51,%52,%53,%54,%55,%56,%57,%58,%59,%60,%61,%62,%63}, "
    "{%64,%65,%66,%67}, %68, p, 1, 1, %70;\n}\n"
    : "+f"(d[0]),"+f"(d[1]),"+f"(d[2]),"+f"(d[3]),"+f"(d[4]),"+f"(d[5]),"+f"(d[6]),"+f"(d[7]),"+f"(d[8]),"+f"(d[9]),"+f"(d[10]),"+f"(d[11]),"+f"(d[12]),"+f"(d[13]),"+f"(d[14]),"+f"(d[15]),"+f"(d[16]),"+f"(d[17]),"+f"(d[18]),"+f"(d[19]),"+f"(d[20]),"+f"(d[21]),"+f"(d[22]),"+f"(d[23]),"+f"(d[24]),"+f"(d[25]),"+f"(d[26]),"+f"(d[27]),"+f"(d[28]),"+f"(d[29]),"+f"(d[30]),"+f"(d[31]),"+f"(d[32]),"+f"(d[33]),"+f"(d[34]),"+f"(d[35]),"+f"(d[36]),"+f"(d[37]),"+f"(d[38]),"+f"(d[39]),"+f"(d[40]),"+f"(d[41]),"+f"(d[42]),"+f"(d[43]),"+f"(d[44]),"+f"(d[45]),"+f"(d[46]),"+f"(d[47]),"+f"(d[48]),"+f"(d[49]),"+f"(d[50]),"+f"(d[51]),"+f"(d[52]),"+f"(d[53]),"+f"(d[54]),"+f"(d[55]),"+f"(d[56]),"+f"(d[57]),"+f"(d[58]),"+f"(d[59]),"+f"(d[60]),"+f"(d[61]),"+f"(d[62]),"+f"(d[63])
    : "r"(a0), "r"(a1), "r"(a2), "r"(a3), "l"(db), "r"(sd), "n"(TB));
}
__device__ __forceinline__ void wgmma_ss(float (&d)[40], uint64_t da, uint64_t db, int sd) {
  asm volatile("{\n.reg .pred p;\nsetp.ne.b32 p, %42, 0;\n"
    "wgmma.mma_async.sync.aligned.m64n80k16.f32.bf16.bf16 "
    "{%0,%1,%2,%3,%4,%5,%6,%7,%8,%9,%10,%11,%12,%13,%14,%15,%16,%17,%18,%19,%20,%21,%22,%23,%24,%25,%26,%27,%28,%29,%30,%31,%32,%33,%34,%35,%36,%37,%38,%39}, "
    "%40, %41, p, 1, 1, 0, 1;\n}\n"
    : "+f"(d[0]),"+f"(d[1]),"+f"(d[2]),"+f"(d[3]),"+f"(d[4]),"+f"(d[5]),"+f"(d[6]),"+f"(d[7]),"+f"(d[8]),"+f"(d[9]),"+f"(d[10]),"+f"(d[11]),"+f"(d[12]),"+f"(d[13]),"+f"(d[14]),"+f"(d[15]),"+f"(d[16]),"+f"(d[17]),"+f"(d[18]),"+f"(d[19]),"+f"(d[20]),"+f"(d[21]),"+f"(d[22]),"+f"(d[23]),"+f"(d[24]),"+f"(d[25]),"+f"(d[26]),"+f"(d[27]),"+f"(d[28]),"+f"(d[29]),"+f"(d[30]),"+f"(d[31]),"+f"(d[32]),"+f"(d[33]),"+f"(d[34]),"+f"(d[35]),"+f"(d[36]),"+f"(d[37]),"+f"(d[38]),"+f"(d[39])
    : "l"(da), "l"(db), "r"(sd));
}
__device__ __forceinline__ void wgmma_ss(float (&d)[56], uint64_t da, uint64_t db, int sd) {
  asm volatile("{\n.reg .pred p;\nsetp.ne.b32 p, %58, 0;\n"
    "wgmma.mma_async.sync.aligned.m64n112k16.f32.bf16.bf16 "
    "{%0,%1,%2,%3,%4,%5,%6,%7,%8,%9,%10,%11,%12,%13,%14,%15,%16,%17,%18,%19,%20,%21,%22,%23,%24,%25,%26,%27,%28,%29,%30,%31,%32,%33,%34,%35,%36,%37,%38,%39,%40,%41,%42,%43,%44,%45,%46,%47,%48,%49,%50,%51,%52,%53,%54,%55}, "
    "%56, %57, p, 1, 1, 0, 1;\n}\n"
    : "+f"(d[0]),"+f"(d[1]),"+f"(d[2]),"+f"(d[3]),"+f"(d[4]),"+f"(d[5]),"+f"(d[6]),"+f"(d[7]),"+f"(d[8]),"+f"(d[9]),"+f"(d[10]),"+f"(d[11]),"+f"(d[12]),"+f"(d[13]),"+f"(d[14]),"+f"(d[15]),"+f"(d[16]),"+f"(d[17]),"+f"(d[18]),"+f"(d[19]),"+f"(d[20]),"+f"(d[21]),"+f"(d[22]),"+f"(d[23]),"+f"(d[24]),"+f"(d[25]),"+f"(d[26]),"+f"(d[27]),"+f"(d[28]),"+f"(d[29]),"+f"(d[30]),"+f"(d[31]),"+f"(d[32]),"+f"(d[33]),"+f"(d[34]),"+f"(d[35]),"+f"(d[36]),"+f"(d[37]),"+f"(d[38]),"+f"(d[39]),"+f"(d[40]),"+f"(d[41]),"+f"(d[42]),"+f"(d[43]),"+f"(d[44]),"+f"(d[45]),"+f"(d[46]),"+f"(d[47]),"+f"(d[48]),"+f"(d[49]),"+f"(d[50]),"+f"(d[51]),"+f"(d[52]),"+f"(d[53]),"+f"(d[54]),"+f"(d[55])
    : "l"(da), "l"(db), "r"(sd));
}
__device__ __forceinline__ void wgmma_ss(float (&d)[60], uint64_t da, uint64_t db, int sd) {
  asm volatile("{\n.reg .pred p;\nsetp.ne.b32 p, %62, 0;\n"
    "wgmma.mma_async.sync.aligned.m64n120k16.f32.bf16.bf16 "
    "{%0,%1,%2,%3,%4,%5,%6,%7,%8,%9,%10,%11,%12,%13,%14,%15,%16,%17,%18,%19,%20,%21,%22,%23,%24,%25,%26,%27,%28,%29,%30,%31,%32,%33,%34,%35,%36,%37,%38,%39,%40,%41,%42,%43,%44,%45,%46,%47,%48,%49,%50,%51,%52,%53,%54,%55,%56,%57,%58,%59}, "
    "%60, %61, p, 1, 1, 0, 1;\n}\n"
    : "+f"(d[0]),"+f"(d[1]),"+f"(d[2]),"+f"(d[3]),"+f"(d[4]),"+f"(d[5]),"+f"(d[6]),"+f"(d[7]),"+f"(d[8]),"+f"(d[9]),"+f"(d[10]),"+f"(d[11]),"+f"(d[12]),"+f"(d[13]),"+f"(d[14]),"+f"(d[15]),"+f"(d[16]),"+f"(d[17]),"+f"(d[18]),"+f"(d[19]),"+f"(d[20]),"+f"(d[21]),"+f"(d[22]),"+f"(d[23]),"+f"(d[24]),"+f"(d[25]),"+f"(d[26]),"+f"(d[27]),"+f"(d[28]),"+f"(d[29]),"+f"(d[30]),"+f"(d[31]),"+f"(d[32]),"+f"(d[33]),"+f"(d[34]),"+f"(d[35]),"+f"(d[36]),"+f"(d[37]),"+f"(d[38]),"+f"(d[39]),"+f"(d[40]),"+f"(d[41]),"+f"(d[42]),"+f"(d[43]),"+f"(d[44]),"+f"(d[45]),"+f"(d[46]),"+f"(d[47]),"+f"(d[48]),"+f"(d[49]),"+f"(d[50]),"+f"(d[51]),"+f"(d[52]),"+f"(d[53]),"+f"(d[54]),"+f"(d[55]),"+f"(d[56]),"+f"(d[57]),"+f"(d[58]),"+f"(d[59])
    : "l"(da), "l"(db), "r"(sd));
}


constexpr int PH_WO = 1, PH_W1 = 2, PH_W2 = 4, PH_QKV = 8;
constexpr int SA = 4, SB = 10, STAGE = 16384;
constexpr int SM_B = SA * STAGE;
constexpr int SM_CS = SM_B + SB * STAGE;
constexpr int SM_B1 = SM_CS + 448;
constexpr int SM_ROW = SM_B1 + 224;
constexpr int SM_BAR = SM_ROW + 2048;
constexpr int CHAIN_SMEM = SM_BAR + 344;
static_assert(CHAIN_SMEM <= 232448, "shared memory");
constexpr int CHAIN_THREADS = 352;
constexpr int BAR_FA = 0, BAR_EA = SA * 8, BAR_FB = 2 * SA * 8, BAR_EB = (2 * SA + SB) * 8, BAR_AUX = (2 * SA + 2 * SB) * 8, BAR_JOB = BAR_AUX + 32,
              BAR_FH = BAR_JOB, BAR_EH = BAR_JOB + 40, BAR_TILE = BAR_JOB + 80;

struct alignas(64) ChainParams {
  CUtensorMap a_x, b_wo, b_w1, b_wqkv, o_out;
  const bf16* xres;
  const bf16* xin;
  const bf16 *b1, *b2;
  unsigned int* flags;
  signed char pref[160];
};

template <int V> struct IC { static constexpr int value = V; };
struct Ring { uint32_t s, ph; };
template <int N> __device__ __forceinline__ void ring_adv(Ring& r) { if (++r.s == N) { r.s = 0; r.ph ^= 1; } }

template <int N, int STRIDE>
__device__ __forceinline__ void produce(int n, uint32_t bytes, uint32_t lim, const uint8_t* src, uint32_t dst, uint32_t full, uint32_t empty, Ring& r) {
#pragma unroll 1
  for (int kt = 0; kt < n; kt++) {
    if (lim) mbar_wait(full + (r.s >= lim ? r.s - lim : r.s + N - lim) * 8, r.s >= lim ? r.ph : r.ph ^ 1);
    mbar_wait(empty + r.s * 8, r.ph ^ 1);
    mbar_expect_tx(full + r.s * 8, bytes);
    bulk_g2s(dst + r.s * STRIDE, src + kt * bytes, bytes, full + r.s * 8);
    ring_adv<N>(r);
  }
}
__device__ __forceinline__ void bulk_s2g(void* dst, uint32_t src, uint32_t bytes) {
  asm volatile("cp.async.bulk.global.shared::cta.bulk_group [%0], [%1], %2;\ncp.async.bulk.commit_group;" ::"l"(dst), "r"(src), "r"(bytes) : "memory");
}
template <int BK, bool B128> __device__ __forceinline__ uint64_t b_desc(uint32_t addr) { return B128 ? mk_desc(addr, 8192, 1024, 1) : mk_desc(addr, BK * 32, 256, 3); }

template <int BN, int MT, int BK, int APT, bool TILED, bool B128, bool HR = false>
__device__ __forceinline__ void mainloop(float (&acc)[MT][BN / 2], uint32_t sbase, uint32_t bars, int lane, int wg, int KT, int a0, bool pass, Ring& rb, int cont = 0) {
  constexpr int NA = HR ? 5 : SA, AST = HR ? 12288 : STAGE, FA = HR ? BAR_FH : BAR_FA, EA = HR ? BAR_EH : BAR_EA;
  Ring ra{(uint32_t)a0 % NA, ((uint32_t)a0 / NA) & 1};
#pragma unroll
  for (int m = 0; m < MT; m++) fence_regs(acc[m]);
  if (HR || a0 != 0) named_bar(6 - wg, 256);
  mbar_wait(bars + BAR_FB + rb.s * 8, rb.ph);
  mbar_wait(bars + FA + ra.s * 8, ra.ph);
  const uint64_t da0 = TILED ? mk_desc(sbase, 128, BK * 16, 0) : mk_desc(sbase, 16, 1024, 1), db0 = b_desc<BK, B128>(sbase + SM_B);
  constexpr int NS = BK / 16, H = MT == 2 ? 1 : 2, KA = TILED ? 16 : 2, KB = B128 ? 128 : 32;
  uint32_t relA = 0, relB = 0;
  uint64_t da = da0 + ra.s * (AST / 16), db = db0 + rb.s * (STAGE / 16);
  auto part = [&](auto k0, auto k1, int sd) {
#pragma unroll
    for (int k = k0.value; k < k1.value; k++)
#pragma unroll
      for (int m = 0; m < MT; m++) wgmma_ss(acc[m], da + m * 512 + k * KA, db + k * KB, k == 0 ? sd : 1);
    wg_commit();
  };
  wg_fence();
  part(IC<0>{}, IC<H>{}, cont);
#pragma unroll 1
  for (int kt = 0; kt < KT - 1; kt++) {
    const bool adv = APT == 1 || (kt & 1);
    const uint32_t curA = adv ? bars + EA + ra.s * 8 : 0, curB = bars + BAR_EB + rb.s * 8;
    if (adv) ring_adv<NA>(ra);
    ring_adv<SB>(rb);
    const uint64_t na = adv ? da0 + ra.s * (AST / 16) : da + 512, nb = db0 + rb.s * (STAGE / 16);
    const bool ok = mbar_test(bars + BAR_FB + rb.s * 8, rb.ph) & mbar_test(bars + FA + ra.s * 8, ra.ph);
    wg_wait<1>();
    mbar_arrive_if(relA, lane == 0 && relA);
    mbar_arrive_if(relB, lane == 0 && relB);
    wg_fence();
    part(IC<H>{}, IC<NS>{}, 1);
    relA = curA; relB = curB; da = na; db = nb;
    if (!ok) { mbar_wait(bars + BAR_FB + rb.s * 8, rb.ph); mbar_wait(bars + FA + ra.s * 8, ra.ph); }
    wg_fence();
    part(IC<0>{}, IC<H>{}, 1);
  }
  if (pass) asm volatile("bar.arrive %0, 256;" ::"r"(5 + wg) : "memory");
  wg_wait<1>();
  mbar_arrive_if(relA, lane == 0 && relA);
  mbar_arrive_if(relB, lane == 0);
  wg_fence();
  part(IC<H>{}, IC<NS>{}, 1);
  relA = bars + EA + ra.s * 8; relB = bars + BAR_EB + rb.s * 8;
  ring_adv<SB>(rb);
  wg_wait<0>();
#pragma unroll
  for (int m = 0; m < MT; m++) fence_regs(acc[m]);
  if (lane == 0) { mbar_arrive(relA); mbar_arrive(relB); }
}
__device__ __forceinline__ void acquire_stage(uint32_t bars, const Ring& rb, uint32_t s) { mbar_wait(bars + BAR_EB + s * 8, s >= rb.s ? rb.ph ^ 1 : rb.ph); }

template <bool FINAL>
__device__ __forceinline__ void epi_resid(const float (&acc)[40], uint32_t (&res)[20], bf16* out, float2* st, uint8_t* stage, int row0, int j, int lane) {
  const int q = lane & 3;
  uint32_t* o0 = FINAL ? (uint32_t*)(stage + (row0 & 63) * 160) + q : (uint32_t*)out + lane;
  float s0 = 0.f, t0 = 0.f, s1 = 0.f, t1 = 0.f;
#pragma unroll
  for (int b = 0; b < 10; b++) {
    res[2 * b] = pack_bf16(acc[4 * b], acc[4 * b + 1]);
    res[2 * b + 1] = pack_bf16(acc[4 * b + 2], acc[4 * b + 3]);
    if (FINAL) { o0[b * 4] = res[2 * b]; o0[b * 4 + 320] = res[2 * b + 1]; }
    else { const int ln = x_line(row0, j * 10 + b); o0[ln * 32] = res[2 * b]; o0[ln * 32 + 256] = res[2 * b + 1]; }
  }
  if (!FINAL) {
#pragma unroll
    for (int b = 0; b < 10; b++) {
      s0 += acc[4 * b] + acc[4 * b + 1]; t0 = fmaf(acc[4 * b], acc[4 * b], fmaf(acc[4 * b + 1], acc[4 * b + 1], t0));
      s1 += acc[4 * b + 2] + acc[4 * b + 3]; t1 = fmaf(acc[4 * b + 2], acc[4 * b + 2], fmaf(acc[4 * b + 3], acc[4 * b + 3], t1));
    }
#pragma unroll
    for (int m = 1; m < 4; m <<= 1) {
      s0 += __shfl_xor_sync(0xffffffffu, s0, m); t0 += __shfl_xor_sync(0xffffffffu, t0, m);
      s1 += __shfl_xor_sync(0xffffffffu, s1, m); t1 += __shfl_xor_sync(0xffffffffu, t1, m);
    }
    if (q < 2) st[j * SEQ + row0 + q * 8] = q ? make_float2(s1, t1) : make_float2(s0, t0);
  }
}
__device__ __forceinline__ void publish(unsigned int* f, int wg, int tid) {
  named_bar(2 + wg, 128);
  if ((tid & 127) == 0) flag_signal(f);
}
__device__ __forceinline__ float gelu_half(float s) {
  const float z = s * fmaf(s * s, 8.f * 0.044715f * 0.7978845608028654f, 2.f * 0.7978845608028654f);
  float th;
  asm("tanh.approx.f32 %0, %1;" : "=f"(th) : "f"(z));
  return fmaf(s, th, s);
}
template <bool DOUBLE> __device__ __forceinline__ float2 row_coef(float s, float t) {
  const float mean = s * (1.f / DM);
  const float var = fmaxf(fmaf(-mean, mean, t * (1.f / DM)), 0.f);
  float r = rsqrtf(var + LN_EPS);
  if (DOUBLE) r *= 0.5f * rsqrtf(var * r * r + LN_EPS);
  return make_float2(r, -r * mean);
}
template <bool DOUBLE, int NP> __device__ __forceinline__ void reduce_stats(const float2* st, float2* dst, int i, int lane) {
  float4 v[2][NP];
#pragma unroll
  for (int rr = 0; rr < 2; rr++)
#pragma unroll
    for (int k = 0; k < NP; k++) v[rr][k] = __ldcg((const float4*)(st + k * SEQ + i * 128 + rr * 64) + lane);
#pragma unroll
  for (int rr = 0; rr < 2; rr++) {
    float s0 = 0.f, t0 = 0.f, s1 = 0.f, t1 = 0.f;
#pragma unroll
    for (int k = 0; k < NP; k++) { s0 += v[rr][k].x; t0 += v[rr][k].y; s1 += v[rr][k].z; t1 += v[rr][k].w; }
    dst[rr * 64 + lane * 2] = row_coef<DOUBLE>(s0, t0);
    dst[rr * 64 + lane * 2 + 1] = row_coef<DOUBLE>(s1, t1);
  }
}

template <int PH, bool FIRST, bool LAST>
__global__ void __launch_bounds__(CHAIN_THREADS, 1) chain_kernel(const __grid_constant__ ChainParams p) {
  extern __shared__ __align__(1024) uint8_t smem[];
  const uint32_t sbase = smem_u32(smem), bars = sbase + SM_BAR;
  float* cs = (float*)(smem + SM_CS);
  uint32_t* sb1 = (uint32_t*)(smem + SM_B1);
  const int tid = threadIdx.x, lane = tid & 31, warp = __shfl_sync(0xffffffffu, tid >> 5, 0);
  if (tid == 32) {
    unsigned int* claim = p.flags + 64;
    uint32_t smid;
    asm volatile("mov.u32 %0, %%smid;" : "=r"(smid));
    int t = smid < 160 ? p.pref[smid] : -1;
    if (t >= 0 && atomicExch(claim + t, 1u) != 0u) t = -2;
    if (t == -1) {
#pragma unroll 1
      for (int it = 0; it < 100000; it++) {
        if (*(volatile unsigned int*)(claim + 128) >= 128u) break;
        __nanosleep(200);
      }
    }
    if (t < 0) {
      t = -1;
      if (*(volatile unsigned int*)(claim + 128) < 128u) {
#pragma unroll 1
        for (int c = 0; c < 128 && t < 0; c++)
          if (atomicExch(claim + c, 1u) == 0u) t = c;
      }
    }
    if (t >= 0) atomicAdd(claim + 128, 1u);
    *(volatile int*)(smem + SM_BAR + BAR_TILE) = t;
  }
  unsigned int* fl = p.flags;
  if (tid == 0) {
    for (int s = 0; s < SA; s++) { mbar_init(bars + BAR_FA + s * 8, 1); mbar_init(bars + BAR_EA + s * 8, 4); }
    for (int s = 0; s < SB; s++) { mbar_init(bars + BAR_FB + s * 8, 1); mbar_init(bars + BAR_EB + s * 8, 8); }
    mbar_init(bars + BAR_AUX, 32); mbar_init(bars + BAR_AUX + 8, 32);
    mbar_init(bars + BAR_AUX + 16, FIRST ? 37 : 32); mbar_init(bars + BAR_AUX + 24, 32);
    for (int s = 0; s < 5; s++) { mbar_init(bars + BAR_FH + s * 8, 1); mbar_init(bars + BAR_EH + s * 8, 4); }
    asm volatile("fence.mbarrier_init.release.cluster;" ::: "memory");
  }
  if (tid == 256) {
    if (FIRST) {
      uint32_t smid;
      asm volatile("mov.u32 %0, %%smid;" : "=r"(smid));
      const int t = smid < 160 ? p.pref[smid] : -1;
      if (t >= 0) {
        asm volatile("cp.async.bulk.prefetch.tensor.2d.L2.global [%0, {%1, %2}];" ::"l"(&p.a_x), "r"(0), "r"((t >> 4) * 256) : "memory");
        asm volatile("cp.async.bulk.prefetch.tensor.3d.L2.global [%0, {%1, %2, %3}];" ::"l"(&p.b_wqkv), "r"(0), "r"(t & 15), "r"(0) : "memory");
        asm volatile("cp.async.bulk.prefetch.tensor.3d.L2.global [%0, {%1, %2, %3}];" ::"l"(&p.b_wqkv), "r"(64), "r"(t & 15), "r"(0) : "memory");
      }
      prefetch_map(&p.b_w1); prefetch_map(&p.b_wo);
    }
    if (LAST) prefetch_map(&p.o_out);
  }
  __syncthreads();
  pdl_launch();
  const int tile = *(volatile int*)(smem + SM_BAR + BAR_TILE);
  if (tile < 0) return;
  const int g = tile >> 4, c = tile & 15;

  if (warp == 9) {
    if (lane == 0) {
      if (FIRST) {
#pragma unroll 1
        for (int kt = 0; kt < 10; kt++) {
          if (kt >= 4) mbar_wait(bars + BAR_FB + (kt - 4) * 8, 0);
          mbar_expect_tx(bars + BAR_FB + kt * 8, STAGE);
          tma_3d(sbase + SM_B + kt * STAGE, &p.b_wqkv, 0, c, kt * 64, bars + BAR_FB + kt * 8);
          tma_3d(sbase + SM_B + kt * STAGE + 8192, &p.b_wqkv, 64, c, kt * 64, bars + BAR_FB + kt * 8);
        }
#pragma unroll 1
        for (int kt = g; kt < 10; kt += 8) {
          mbar_wait(bars + BAR_FB + kt * 8, 0);
          bulk_s2g(g_wt + WT_QKV + (c * 10 + kt) * STAGE, sbase + SM_B + kt * STAGE, STAGE);
        }
        asm volatile("cp.async.bulk.wait_group.read 0;" ::: "memory");
        mbar_arrive(bars + BAR_AUX + 16);
        asm volatile("cp.async.bulk.wait_group 0;" ::: "memory");
      } else {
        Ring r{0, 0};
#pragma unroll 1
        for (int ph = 0; ph < ((PH & PH_QKV) ? 4 : 3); ph++) {
          if (ph == 2) pdl_wait();
          const uint32_t bytes = ph == 0 ? 10240 : (ph == 1 ? 14336 : (ph == 2 ? 15360 : STAGE));
          const int n = ph == 2 ? 18 : 10, off = ph == 0 ? WT_WO : (ph == 1 ? WT_W1 : (ph == 2 ? WT_W2 : WT_QKV));
          produce<SB, STAGE>(n, bytes, ph == 0 ? 0 : (ph == 2 ? 3 : 2), g_wt + off + ((ph & 1) ? c : c >> 1) * n * bytes, sbase + SM_B, bars + BAR_FB,
                             bars + BAR_EB, r);
        }
      }
    }
  } else if (warp == 8) {
    if (lane == 0) {
      Ring r{0, 0};
      if (FIRST) {
#pragma unroll 1
        for (int t = 0; t < 20; t++) {
          mbar_wait(bars + BAR_EA + r.s * 8, r.ph ^ 1);
          mbar_expect_tx(bars + BAR_FA + r.s * 8, STAGE);
          tma_2d(sbase + r.s * STAGE, &p.a_x, (t % 10) * 64, g * 256 + (t / 10) * 128, bars + BAR_FA + r.s * 8);
          ring_adv<SA>(r);
        }
#pragma unroll 1
        for (int job = tile; job < 240; job += 128) {
          const int n = job >> 7;
          mbar_wait(bars + BAR_EB + (3 + n) * 8, 0);
          mbar_expect_tx(bars + BAR_JOB + n * 8, job < 160 ? 14336 : 10240);
#pragma unroll 1
          for (int b = 0; b < (job < 160 ? 7 : 5); b++)
            tma_3d(sbase + SM_B + (3 + n) * STAGE + b * 2048, job < 160 ? &p.b_w1 : &p.b_wo, (job < 160 ? ((job / 10) & 1) * 112 : 0) + b * 16,
                   job < 160 ? job / 20 : job / 10 - 16, (job % 10) * 64, bars + BAR_JOB + n * 8);
        }
#pragma unroll 1
        for (int job = tile; job < 240; job += 128) {
          mbar_wait(bars + BAR_JOB + (job >> 7) * 8, 0);
          bulk_s2g(g_wt + (job < 160 ? WT_W1 + job * 14336 : WT_WO + (job - 160) * 10240), sbase + SM_B + (3 + (job >> 7)) * STAGE, job < 160 ? 14336 : 10240);
        }
        asm volatile("cp.async.bulk.wait_group 0;" ::: "memory");
      } else {
        pdl_wait();
#pragma unroll 1
        for (int ph = 0; ph < ((PH & PH_QKV) ? 3 : 2); ph++) {
#pragma unroll 1
          for (int s = 0; s < 2; s++) {
            if (ph) { flag_wait(fl + (ph - 1) * 32 + g * 2 + s, 16); fence_async_global(); }
            const uint8_t* src = ph == 0 ? (const uint8_t*)g_o + (g * 4 + s * 2 + (c & 1)) * 81920 : (const uint8_t*)(ph == 1 ? g_x1 : g_x2) + (g * 2 + s) * 163840;
            produce<SA, STAGE>(ph ? 10 : 5, 16384, 0, src, sbase, bars + BAR_FA, bars + BAR_EA, r);
          }
          if (ph == 1) {
            Ring rh{0, 0};
#pragma unroll 1
            for (int s = 0; s < SA; s++) mbar_wait(bars + BAR_EA + s * 8, s >= r.s ? r.ph ^ 1 : r.ph);
#pragma unroll 1
            for (int s = 0; s < 4; s++) {
              if (s < 2) { flag_wait(fl + 16 + g * 2 + s, 16); fence_async_global(); }
              produce<5, 12288>(s < 2 ? 10 : 8, 12288, 0, (const uint8_t*)g_h + ((g * 4 + (s & 1) * 2 + (c & 1)) * 18 + (s >> 1) * 10) * 12288, sbase, bars + BAR_FH,
                                bars + BAR_EH, rh);
            }
#pragma unroll 1
            for (int s = 0; s < 5; s++) mbar_wait(bars + BAR_EH + s * 8, s >= rh.s ? rh.ph ^ 1 : rh.ph);
          }
        }
      }
    }
  } else if (warp == 10) {
    float2* srow = (float2*)(smem + SM_ROW);
    if (FIRST) {
      named_bar(4, 160);
      if (lane == 0) flag_signal(fl + g * 2 + (c >> 3));
#pragma unroll 1
      for (int s = 0; s < 2; s++) {
        if (lane == 0) flag_wait(fl + g * 2 + s, 8);
        __syncwarp();
        reduce_stats<false, 2>(g_s.st0, srow + s * 128, g * 2 + s, lane);
        mbar_arrive(bars + BAR_AUX + 16 + s * 8);
      }
#pragma unroll 1
      for (int n = 0; n < 2; n++) {
        const int job = n * 128 + tile;
        if (job < 160) {
          mbar_wait(bars + BAR_JOB + n * 8, 0);
          const uint8_t* base = smem + SM_B + (3 + n) * STAGE + ((lane & 15) >> 1) * 2048 + (lane >> 4) * 1024;
          float a[8];
#pragma unroll
          for (int e = 0; e < 8; e++) a[e] = 0.f;
#pragma unroll 4
          for (int r = 0; r < 32; r++) {
            const uint4 v = *(const uint4*)(base + r * 32 + (((lane & 1) ^ ((r >> 2) & 1)) * 16));
            a[0] += bf_lo(v.x); a[1] += bf_hi(v.x); a[2] += bf_lo(v.y); a[3] += bf_hi(v.y);
            a[4] += bf_lo(v.z); a[5] += bf_hi(v.z); a[6] += bf_lo(v.w); a[7] += bf_hi(v.w);
          }
#pragma unroll
          for (int e = 0; e < 8; e++) a[e] += __shfl_xor_sync(0xffffffffu, a[e], 16);
          if (lane < 14) {
            float4* d = (float4*)(g_s.csp_w1 + (job % 10) * 1792 + (job / 10) * 112 + lane * 8);
            d[0] = make_float4(a[0], a[1], a[2], a[3]); d[1] = make_float4(a[4], a[5], a[6], a[7]);
          }
        }
      }
    } else {
      if (lane < 28) {
        float4 v[10], a = make_float4(0.f, 0.f, 0.f, 0.f);
#pragma unroll
        for (int k = 0; k < 10; k++) v[k] = __ldcg((const float4*)(g_s.csp_w1 + k * 1792 + c * 112) + lane);
#pragma unroll
        for (int k = 0; k < 10; k++) { a.x += v[k].x; a.y += v[k].y; a.z += v[k].z; a.w += v[k].w; }
        ((float4*)cs)[lane] = a;
      }
      for (int k = lane; k < 56; k += 32) {
        const int col = (c >> 1) * 216 + (c & 1) * 112 + k * 2;
        const uint32_t v = col < FF ? __ldg((const uint32_t*)(p.b1 + col)) : 0u;
        sb1[k] = pack_bf16(0.5f * bf_lo(v), 0.5f * bf_hi(v));
      }
#pragma unroll 1
      for (int s = 0; s < 2; s++) {
        if (lane == 0) flag_wait(fl + g * 2 + s, 16);
        __syncwarp();
        reduce_stats<true, 8>(g_s.st1, srow + s * 128, g * 2 + s, lane);
        mbar_arrive(bars + BAR_AUX + s * 8);
      }
      if (PH & PH_QKV) {
        const float4 cq = lane < 30 ? __ldcg((const float4*)(g_s.cs_qkv + c * 120) + lane) : make_float4(0.f, 0.f, 0.f, 0.f);
#pragma unroll 1
        for (int s = 0; s < 2; s++) {
          if (lane == 0) { if (s == 0) flag_wait(fl + 16 + g * 2 + 1, 16); flag_wait(fl + 32 + g * 2 + s, 16); }
          __syncwarp();
          if (s == 0 && lane < 30) ((float4*)cs)[lane] = cq;
          reduce_stats<false, 8>(g_s.st2, srow + s * 128, g * 2 + s, lane);
          mbar_arrive(bars + BAR_AUX + 16 + s * 8);
        }
      }
    }
  } else {
    const int wg = warp >> 2, w4 = warp & 3, q = lane & 3;
    const int rbk = g * 2 + wg, rl = w4 * 16 + (lane >> 2);
    const int rowS = rbk * 128 + (c & 1) * 64 + rl, jS = c >> 1;
    const float2* srow = (const float2*)(smem + SM_ROW) + wg * 128;
    const bool t0 = (tid & 127) == 0;
    Ring rb{0, 0};
    uint32_t res[20];
    if (FIRST) {
      if (wg == 1) {
        const int xrow = g * 256 + c * 16 + (w4 & 1) * 8 + (lane >> 2), xcg = (w4 >> 1) * 40 + q;
        uint4 xv[10];
#pragma unroll
        for (int k = 0; k < 10; k++) xv[k] = __ldg((const uint4*)(p.xin + (size_t)xrow * DM) + xcg + k * 4);
        float xs = 0.f, xt = 0.f;
#pragma unroll
        for (int k = 0; k < 10; k++) {
          const uint32_t e[4] = {xv[k].x, xv[k].y, xv[k].z, xv[k].w};
#pragma unroll
          for (int m = 0; m < 4; m++) { const float a = bf_lo(e[m]), b = bf_hi(e[m]); xs += a + b; xt = fmaf(a, a, fmaf(b, b, xt)); }
        }
#pragma unroll
        for (int m = 1; m < 4; m <<= 1) { xs += __shfl_xor_sync(0xffffffffu, xs, m); xt += __shfl_xor_sync(0xffffffffu, xt, m); }
        if (q == 0) g_s.st0[(w4 >> 1) * SEQ + xrow] = make_float2(xs, xt);
        asm volatile("bar.arrive 4, 160;" ::: "memory");
#pragma unroll
        for (int k = 0; k < 10; k++) *((uint4*)g_x0 + x_line(xrow, xcg + k * 4) * 8 + (xrow & 7)) = xv[k];
        float o[60];
        const uint32_t one = 0x3F803F80u;
#pragma unroll 1
        for (int kt = 0; kt < 10; kt++) {
          mbar_wait(bars + BAR_FB + kt * 8, 0);
          wg_fence();
#pragma unroll
          for (int k = 0; k < 4; k++) wgmma_rs_n120<1>(o, one, one, one, one, b_desc<64, true>(sbase + SM_B + kt * STAGE) + k * 128, (kt | k) != 0);
          wg_commit();
        }
        wg_wait<0>();
        fence_regs(o);
        if ((tid & 127) < 4) {
#pragma unroll
          for (int b = 0; b < 15; b++) {
            *(float2*)(cs + b * 8 + q * 2) = make_float2(o[4 * b], o[4 * b + 1]);
            if (g == 0) *(float2*)(g_s.cs_qkv + c * 120 + b * 8 + q * 2) = make_float2(o[4 * b], o[4 * b + 1]);
          }
          mbar_arrive(bars + BAR_AUX + 16);
        }
        named_bar(3, 128);
      }
    } else {
#pragma unroll
      for (int b = 0; b < 10; b++) {
        const uint32_t* r0 = (const uint32_t*)p.xres + x_line(rowS, jS * 10 + b) * 32 + lane;
        res[2 * b] = __ldcg(r0); res[2 * b + 1] = __ldcg(r0 + 256);
      }
      {
        float acc[1][40];
#pragma unroll
        for (int b = 0; b < 20; b++) { acc[0][2 * b] = bf_lo(res[b]); acc[0][2 * b + 1] = bf_hi(res[b]); }
        mainloop<80, 1, 64, 2, true, false>(acc, sbase, bars, lane, wg, 10, wg * 5, wg != 0, rb, 1);
        epi_resid<false>(acc[0], res, g_x1, g_s.st1, smem, rowS, jS, lane);
        if (wg == 0) asm volatile("bar.arrive 5, 256;" ::: "memory");
        publish(fl + rbk, wg, tid);
      }
      {
        float acc[2][56];
        mainloop<112, 2, 64, 1, true, false>(acc, sbase, bars, lane, wg, 10, 10 + wg * 10, true, rb);
        mbar_wait(bars + BAR_AUX + wg * 8, 0);
        const float2 c0 = srow[rl], c1 = srow[rl + 8], c2 = srow[rl + 64], c3 = srow[rl + 72];
        const int cg0 = (c >> 1) * 27 + (c & 1) * 14;
        uint32_t* o0 = (uint32_t*)g_h + h_line(rbk * 128 + rl, cg0) * 32 + lane;
        int kg = cg0 % 12;
#pragma unroll
        for (int b = 0; b < 14; b++) {
          if (b < 13 || !(c & 1)) {
            const float2 cc = *(const float2*)(cs + b * 8 + q * 2);
            const uint32_t bb = sb1[b * 4 + q];
            const float bl = bf_lo(bb), bh = bf_hi(bb);
            o0[0] = pack_bf16(gelu_half(fmaf(c0.x, acc[0][4 * b], fmaf(c0.y, cc.x, bl))), gelu_half(fmaf(c0.x, acc[0][4 * b + 1], fmaf(c0.y, cc.y, bh))));
            o0[384] = pack_bf16(gelu_half(fmaf(c1.x, acc[0][4 * b + 2], fmaf(c1.y, cc.x, bl))), gelu_half(fmaf(c1.x, acc[0][4 * b + 3], fmaf(c1.y, cc.y, bh))));
            o0[18 * 3072] = pack_bf16(gelu_half(fmaf(c2.x, acc[1][4 * b], fmaf(c2.y, cc.x, bl))), gelu_half(fmaf(c2.x, acc[1][4 * b + 1], fmaf(c2.y, cc.y, bh))));
            o0[18 * 3072 + 384] = pack_bf16(gelu_half(fmaf(c3.x, acc[1][4 * b + 2], fmaf(c3.y, cc.x, bl))), gelu_half(fmaf(c3.x, acc[1][4 * b + 3], fmaf(c3.y, cc.y, bh))));
            o0 += (++kg == 12) ? (96 - 11) * 32 : 32;
            if (kg == 12) kg = 0;
          }
        }
        publish(fl + 16 + rbk, wg, tid);
      }
      {
        float acc[1][40];
#pragma unroll
        for (int b = 0; b < 10; b++) {
          const uint32_t bb = __ldg((const uint32_t*)(p.b2 + jS * 80) + b * 4 + q);
          acc[0][4 * b] = bf_lo(res[2 * b]) + bf_lo(bb); acc[0][4 * b + 1] = bf_hi(res[2 * b]) + bf_hi(bb);
          acc[0][4 * b + 2] = bf_lo(res[2 * b + 1]) + bf_lo(bb); acc[0][4 * b + 3] = bf_hi(res[2 * b + 1]) + bf_hi(bb);
        }
#pragma unroll 1
        for (int sg = 0; sg < 2; sg++)
          mainloop<80, 1, 96, 1, true, false, true>(acc, sbase, bars, lane, wg, sg ? 8 : 10, sg ? 20 + wg * 8 : wg * 10, !sg || (LAST ? wg == 0 : wg != 0), rb, 1);
        if (LAST) {
          const uint32_t st = (rb.s + wg) % SB;
          acquire_stage(bars, rb, st);
          epi_resid<true>(acc[0], res, nullptr, nullptr, smem + SM_B + st * STAGE, rowS, jS, lane);
          asm volatile("fence.proxy.async.shared::cta;" ::: "memory");
          named_bar(2 + wg, 128);
          if (t0) {
            asm volatile("cp.async.bulk.tensor.2d.global.shared::cta.bulk_group [%0, {%2, %3}], [%1];" ::"l"(&p.o_out), "r"(sbase + SM_B + st * STAGE), "r"(jS * 80),
                         "r"(rbk * 128 + (c & 1) * 64) : "memory");
            asm volatile("cp.async.bulk.commit_group;\ncp.async.bulk.wait_group 0;" ::: "memory");
          }
        } else {
          epi_resid<false>(acc[0], res, g_x2, g_s.st2, smem, rowS, jS, lane);
          if (wg == 0) asm volatile("bar.arrive 5, 256;" ::: "memory");
          publish(fl + 32 + rbk, wg, tid);
        }
      }
    }
    if (PH & PH_QKV) {
      float acc[2][60];
      mainloop<120, 2, 64, 1, !FIRST, true>(acc, sbase, bars, lane, wg, 10, (FIRST ? 0 : 30) + wg * 10, wg == 0, rb);
      mbar_wait(bars + BAR_AUX + 16 + wg * 8, 0);
      pdl_wait();
      const float QS = 0.22360679774997896f * 1.4426950408889634f;
      unsigned int* smax = sb1 + 16 + wg * 8;
      if ((tid & 127) < 6) smax[tid & 127] = 0u;
      named_bar(2 + wg, 128);
      int off[5];
#pragma unroll
      for (int m = 0; m < 5; m++) {
        const int cc = m * 8 + q * 2, hh = cc >= 20, d = cc - hh * 20;
        off[m] = hh * 6144 + (d >> 3) * 128 + (d & 7) * 2;
      }
#pragma unroll
      for (int pr = 0; pr < 3; pr++) {
        const int part = (c * 6 + pr * 2) >> 5;
        float nrm[2];
        const uint32_t sst = (rb.s + pr) % SB, soff = wg ? pr * STAGE : SM_B + sst * STAGE;
        if (wg == 0) acquire_stage(bars, rb, sst);
        uint8_t* stg = smem + soff + w4 * 768 + (lane >> 2) * 16;
#pragma unroll
        for (int mt = 0; mt < 2; mt++) {
          const float2 c0 = srow[mt * 64 + rl], c1 = srow[mt * 64 + rl + 8];
          const bool mu0 = is_mufu(mt * 8 + w4 * 2), mu1 = is_mufu(mt * 8 + w4 * 2 + 1), mu = (q & 1) ? mu1 : mu0;
          const float s0 = part == 0 ? QS : (part == 1 && !mu0 ? 0x1p-22f : 1.f), s1 = part == 0 ? QS : (part == 1 && !mu1 ? 0x1p-22f : 1.f);
          const float a0 = c0.x * s0, b0 = c0.y * s0, a1 = c1.x * s1, b1 = c1.y * s1;
          float nA0 = 0.f, nA1 = 0.f, nB0 = 0.f, nB1 = 0.f;
#pragma unroll
          for (int m = 0; m < 5; m++) {
            const int b = pr * 5 + m;
            const float2 cc = *(const float2*)(cs + b * 8 + q * 2);
            uint8_t* ptr = stg + off[m] + mt * 3072;
            const float v0 = fmaf(a0, acc[mt][4 * b], b0 * cc.x), v1 = fmaf(a0, acc[mt][4 * b + 1], b0 * cc.y);
            const float v2 = fmaf(a1, acc[mt][4 * b + 2], b1 * cc.x), v3 = fmaf(a1, acc[mt][4 * b + 3], b1 * cc.y);
            *(uint32_t*)ptr = pack_bf16(v0, v1);
            *(uint32_t*)(ptr + 384) = pack_bf16(v2, v3);
            const float n0 = fmaf(v0, v0, v1 * v1), n1 = fmaf(v2, v2, v3 * v3);
            if (m < 2) { nA0 += n0; nA1 += n1; } else if (m > 2) { nB0 += n0; nB1 += n1; }
            else if (q < 2) { nA0 += n0; nA1 += n1; } else { nB0 += n0; nB1 += n1; }
          }
          const uint2 ex = part == 0 ? make_uint2(0x3F803F80u, 0x00003F80u)
                                     : (part == 1 ? (mu ? make_uint2(0u, 0u) : make_uint2(0x377C3C00u, 0x00003020u)) : make_uint2(0x00003F80u, 0u));
          *(uint2*)(stg + mt * 3072 + (q >> 1) * 6144 + (q & 1) * 384 + 264) = ex;
          float x = (q & 1) ? nA1 : nA0, y = (q & 1) ? nB1 : nB0;
          x += __shfl_xor_sync(0xffffffffu, (q & 1) ? nA0 : nA1, 1);
          y += __shfl_xor_sync(0xffffffffu, (q & 1) ? nB0 : nB1, 1);
          float n = (q & 2) ? y : x;
          n += __shfl_xor_sync(0xffffffffu, (q & 2) ? x : y, 2);
          nrm[mt] = (part == 1 && !mu) ? n * 0x1p44f : n;
        }
        asm volatile("fence.proxy.async.shared::cta;" ::: "memory");
        named_bar(2 + wg, 128);
        if ((tid & 127) < 2) bulk_s2g((uint8_t*)g_qkv + (size_t)(c * 6 + pr * 2 + lane) * HEAD_BYTES + rbk * 6144, sbase + soff + lane * 6144, 6144);
        if (part < 2) atomicMax(smax + pr * 2 + (q >> 1), max(__float_as_uint(nrm[0]) & 0x7FFFFFFFu, __float_as_uint(nrm[1]) & 0x7FFFFFFFu));
      }
      named_bar(2 + wg, 128);
      if ((tid & 127) < 6 && c * 6 + (tid & 127) < 64) atomicMax(fl + NORM_OFF + c * 6 + (tid & 127), smax[tid & 127]);
      if ((tid & 127) < 2) {
        asm volatile("cp.async.bulk.wait_group 0;" ::: "memory");
      }
    }
  }
}

__device__ __forceinline__ uint32_t exp2_poly_pair(float a0, float a1) {
  const uint32_t v = __byte_perm(__float_as_uint(a0), __float_as_uint(a1), 0x7430);
  const uint32_t e = __byte_perm(__float_as_uint(a0), __float_as_uint(a1), 0x6521);
  uint32_t u;
  asm("fma.rn.f16x2 %0, %1, %2, %3;" : "=r"(u) : "r"(v), "r"(0x1d611d61u), "r"(0xa012a012u));
  asm("fma.rn.f16x2 %0, %1, %2, %3;" : "=r"(u) : "r"(u), "r"(v), "r"(0x21622162u));
  uint32_t r;
  asm("{\n.reg .b32 t;\nshl.b32 t, %1, 7;\nadd.u32 %0, t, %2;\n}" : "=r"(r) : "r"(e), "r"(u));
  return r;
}
constexpr int KPITCH = 6144 + 128;
constexpr int ATT_V = 16 * KPITCH, ATT_JOB = ATT_V + HEAD_BYTES, ATT_BAR = ATT_JOB + 2 * 15360, ATT_SMEM = ATT_BAR + 128;

__device__ __forceinline__ void att_store(const float (&O)[12], int row0, int h, int lane) {
  const float l0 = __shfl_sync(0xffffffffu, O[8], (lane & ~3) | 2), l1 = __shfl_sync(0xffffffffu, O[10], (lane & ~3) | 2);
  const float r0 = __fdividef(1.f, l0), r1 = __fdividef(1.f, l1);
#pragma unroll
  for (int c = 0; c < 3; c++)
    if (c < 2 || (lane & 3) < 2) {
      const int col = h * 20 + c * 8 + (lane & 3) * 2;
      uint32_t* o0 = (uint32_t*)g_o + o_line(row0, col >> 3) * 32 + (row0 & 7) * 4 + ((col & 7) >> 1);
      o0[0] = pack_bf16(O[4 * c] * r0, O[4 * c + 1] * r0);
      o0[256] = pack_bf16(O[4 * c + 2] * r1, O[4 * c + 3] * r1);
    }
}

struct alignas(64) AttParams {
  CUtensorMap b_w2;
  const unsigned int* norms;
  unsigned int *reset_a, *reset_b, *reset_c;
  const uint32_t* zeros;
  int jobs;
};
__global__ void __launch_bounds__(512, 1) att_kernel(const __grid_constant__ AttParams p) {
  const unsigned int* norms = p.norms;
  extern __shared__ __align__(1024) uint8_t smem[];
  const uint32_t sK = smem_u32(smem), sV = sK + ATT_V, bars = sK + ATT_BAR;
  const int h = blockIdx.x >> 2, qt = blockIdx.x & 3;
  const int tid = threadIdx.x, lane = tid & 31, wg = __shfl_sync(0xffffffffu, tid >> 7, 0), warp = (tid >> 5) & 3;
  if (tid == 0) {
    for (int c = 0; c < 9; c++) mbar_init(bars + c * 8, 1);
    asm volatile("fence.mbarrier_init.release.cluster;" ::: "memory");
  }
  *(uint32_t*)(smem + (tid >> 5) * KPITCH + 6144 + lane * 4) = 0u;
  asm volatile("fence.proxy.async;" ::: "memory");
  const uint32_t z0 = __ldg(p.zeros + (tid & 1)), z1 = __ldg(p.zeros + 2 + (tid & 1));
  __syncthreads();
  pdl_wait();
  pdl_launch();
  const uint8_t* gq = (const uint8_t*)g_qkv + (size_t)h * HEAD_BYTES;
  const uint64_t dK = mk_desc(sK, 128, 384, 0);
  const uint64_t dV = mk_desc(sV, 384, 128, 0);
  uint32_t q[6];
  auto load_q = [&](int row0) {
    const uint32_t* qa = (const uint32_t*)(gq + (row0 >> 3) * 384 + (row0 & 7) * 16) + (lane & 3);
    q[0] = __ldcg(qa); q[1] = __ldcg(qa + 96); q[2] = __ldcg(qa + 32); q[3] = __ldcg(qa + 128); q[4] = __ldcg(qa + 64); q[5] = __ldcg(qa + 160);
  };
  const int rowA = qt * 512 + wg * 64 + warp * 16 + (lane >> 2);
  load_q(rowA);
  auto load_kv = [&](int c) {
    mbar_expect_tx(bars + c * 8, 24576);
    bulk_g2s(sK + c * 2 * KPITCH, gq + 32 * HEAD_BYTES + c * 12288, 6144, bars + c * 8);
    bulk_g2s(sK + (c * 2 + 1) * KPITCH, gq + 32 * HEAD_BYTES + c * 12288 + 6144, 6144, bars + c * 8);
    bulk_g2s(sV + c * 12288, gq + 64 * HEAD_BYTES + c * 12288, 12288, bars + c * 8);
  };
  if (tid == 480) { load_kv(0); load_kv(1); }
  __syncwarp();
  auto load_rest = [&]() {
        if (tid == 480) {
#pragma unroll 1
          for (int c = 2; c < 8; c++) load_kv(c);
          if (p.jobs) {
            mbar_expect_tx(bars + 64, blockIdx.x < 16 ? 30720 : 15360);
#pragma unroll 1
            for (int job = blockIdx.x; job < 144; job += 128)
#pragma unroll 1
              for (int b = 0; b < 5; b++) tma_3d(sK + ATT_JOB + (job >> 7) * 15360 + b * 3072, &p.b_w2, b * 16, job / 18, (job % 18) * 96, bars + 64);
          }
        }
        __syncwarp();
  };
  const bool unsafe = !(__uint_as_float(__ldcg(norms + h)) * __uint_as_float(__ldcg(norms + 32 + h)) <= 3500.f);
  if (blockIdx.x == 0 && tid < NORM_OFF) { p.reset_a[tid] = 0u; if (tid < FLAG_SET - NORM_OFF) p.reset_b[tid] = 0u; if (p.reset_c) p.reset_c[tid] = 0u; }
  auto fast_tile = [&](auto first, int row0) -> bool {
      constexpr int tt = first.value ? 0 : 1;
      float S[64], O[12];
      uint32_t P[32];
#pragma unroll
      for (int k = 0; k < 64; k++) S[k] = 0.f;
#pragma unroll
      for (int k = 0; k < 12; k++) O[k] = 0.f;
      auto blocks = [&](int g0, int g1) {
        uint64_t gk = dK + g0 * (KPITCH / 16), gv = dV + g0 * 384;
#pragma unroll 1
        for (int g = g0; g < g1; g++) {
        if (tt == 0 && (g & 1) == 0) mbar_wait_warp(bars + (g >> 1) * 8, 0);
        wg_fence();
        wgmma_rs_n128<0>(S, q[0], q[1], q[2], q[3], gk, 0);
        wgmma_rs_n128<0>(S, q[4], q[5], z0, z1, gk + 16, 1);
        wg_commit();
        wg_wait<0>();
        fence_regs(S);
#pragma unroll
        for (int hf = 0; hf < 8; hf++) {
          constexpr int NB = 16 / 8;
          uint32_t (&Ph)[2 * NB] = *(uint32_t(*)[2 * NB])(P + hf * 2 * NB);
#pragma unroll
          for (int b = hf * NB; b < hf * NB + NB; b++) {
            if (is_mufu(b)) { P[2 * b] = pack_bf16(ex2(S[4 * b]), ex2(S[4 * b + 1])); P[2 * b + 1] = pack_bf16(ex2(S[4 * b + 2]), ex2(S[4 * b + 3])); }
            else { P[2 * b] = exp2_poly_pair(S[4 * b], S[4 * b + 1]); P[2 * b + 1] = exp2_poly_pair(S[4 * b + 2], S[4 * b + 3]); }
          }
          fence_regs(Ph);
          wg_fence();
#pragma unroll
          for (int s = hf * NB / 2; s < (hf + 1) * NB / 2; s++) wgmma_rs_n24<1>(O, P[4 * s], P[4 * s + 1], P[4 * s + 2], P[4 * s + 3], gv + s * 48, 1);
          wg_commit();
        }
        wg_wait<0>();
        gk += KPITCH / 16; gv += 384;
        }
      };
      if (tt == 0) {
        blocks(0, 2);
        load_rest();
        blocks(2, 16);
      } else blocks(0, 16);
      fence_regs(O);
      att_store(O, row0, h, lane);
      bool bad = false;
      float m = 0.f;
#pragma unroll
      for (int k = 0; k < 12; k++) { m = fmaxf(m, fabsf(O[k])); bad |= (O[k] != O[k]); }
      bad |= !(m <= 3e38f);
      if ((lane & 3) == 2) bad |= !(O[8] >= 0x1p-20f) || !(O[10] >= 0x1p-20f);
      uint32_t r;
      asm volatile("{\n.reg .pred p, r;\nsetp.ne.u32 p, %1, 0;\nbarrier.red.or.pred.aligned r, %2, 128, p;\nselp.u32 %0, 1, 0, r;\n}\n" : "=r"(r) : "r"((uint32_t)bad), "r"(1 + wg) : "memory");
      return r != 0;
  };
  auto safe_tile = [&](int row0) {
      float S[64], O[12];
      uint32_t P[32];
#pragma unroll
      for (int k = 0; k < 64; k++) S[k] = 0.f;
      if ((lane & 3) >= 2) { q[4] = 0u; q[5] = 0u; }
      float m0 = -INFINITY, m1 = -INFINITY;
#pragma unroll
      for (int k = 0; k < 12; k++) O[k] = 0.f;
      uint64_t gk = dK, gv = dV;
#pragma unroll 1
      for (int g = 0; g < 16; g++) {
        wg_fence();
        wgmma_rs_n128<0>(S, q[0], q[1], q[2], q[3], gk, 0);
        wgmma_rs_n128<0>(S, q[4], q[5], z0, z1, gk + 16, 1);
        wg_commit();
        wg_wait<0>();
        fence_regs(S);
        float x0 = m0, x1 = m1;
#pragma unroll
        for (int b = 0; b < 16; b++) {
          if (!is_mufu(b)) { S[4 * b] *= 0x1p22f; S[4 * b + 1] *= 0x1p22f; S[4 * b + 2] *= 0x1p22f; S[4 * b + 3] *= 0x1p22f; }
          x0 = fmaxf(x0, fmaxf(S[4 * b], S[4 * b + 1]));
          x1 = fmaxf(x1, fmaxf(S[4 * b + 2], S[4 * b + 3]));
        }
        x0 = fmaxf(x0, __shfl_xor_sync(0xffffffffu, x0, 1)); x1 = fmaxf(x1, __shfl_xor_sync(0xffffffffu, x1, 1));
        x0 = fmaxf(x0, __shfl_xor_sync(0xffffffffu, x0, 2)); x1 = fmaxf(x1, __shfl_xor_sync(0xffffffffu, x1, 2));
        const float al0 = ex2(m0 - x0), al1 = ex2(m1 - x1);
        m0 = x0; m1 = x1;
#pragma unroll
        for (int c = 0; c < 3; c++) { O[4 * c] *= al0; O[4 * c + 1] *= al0; O[4 * c + 2] *= al1; O[4 * c + 3] *= al1; }
#pragma unroll
        for (int b = 0; b < 16; b++) {
          P[2 * b] = pack_bf16(ex2(S[4 * b] - m0), ex2(S[4 * b + 1] - m0));
          P[2 * b + 1] = pack_bf16(ex2(S[4 * b + 2] - m1), ex2(S[4 * b + 3] - m1));
        }
        fence_regs(P);
        fence_regs(O);
        wg_fence();
#pragma unroll
        for (int s = 0; s < 8; s++) wgmma_rs_n24<1>(O, P[4 * s], P[4 * s + 1], P[4 * s + 2], P[4 * s + 3], gv + s * 48, 1);
        wg_commit();
        wg_wait<0>();
        fence_regs(O);
        gk += KPITCH / 16; gv += 384;
      }
      att_store(O, row0, h, lane);
      named_bar(1 + wg, 128);
  };
  bool redo = true;
  if (!__any_sync(0xffffffffu, unsafe)) redo = fast_tile(IC<1>{}, rowA);
  else {
    load_rest();
#pragma unroll 1
    for (int c = 0; c < 8; c++) mbar_wait(bars + c * 8, 0);
  }
  if (__any_sync(0xffffffffu, redo)) safe_tile(rowA);
  load_q(rowA + 256);
  if (tid == 480 && p.jobs) {
    mbar_wait(bars + 64, 0);
#pragma unroll 1
    for (int job = blockIdx.x; job < 144; job += 128) bulk_s2g(g_wt + WT_W2 + job * 15360, sK + ATT_JOB + (job >> 7) * 15360, 15360);
  }
  __syncwarp();
  redo = true;
  if (!__any_sync(0xffffffffu, unsafe)) redo = fast_tile(IC<0>{}, rowA + 256);
  if (__any_sync(0xffffffffu, redo)) safe_tile(rowA + 256);
  if (tid == 480) asm volatile("cp.async.bulk.wait_group 0;" ::: "memory");
}

typedef CUresult (*EncodeFn)(CUtensorMap*, CUtensorMapDataType, cuuint32_t, void*, const cuuint64_t*, const cuuint64_t*, const cuuint32_t*,
                             const cuuint32_t*, CUtensorMapInterleave, CUtensorMapSwizzle, CUtensorMapL2promotion, CUtensorMapFloatOOBfill);

static void make_a(EncodeFn enc, CUtensorMap* m, const void* ptr, int K) {
  cuuint64_t dims[2] = {(cuuint64_t)K, (cuuint64_t)SEQ}, strides[1] = {(cuuint64_t)K * 2};
  cuuint32_t box[2] = {64, 128}, es[2] = {1, 1};
  enc(m, CU_TENSOR_MAP_DATA_TYPE_BFLOAT16, 2, (void*)ptr, dims, strides, box, es, CU_TENSOR_MAP_INTERLEAVE_NONE, CU_TENSOR_MAP_SWIZZLE_128B,
      CU_TENSOR_MAP_L2_PROMOTION_NONE, CU_TENSOR_MAP_FLOAT_OOB_FILL_NONE);
}
static void make_out(EncodeFn enc, CUtensorMap* m, void* ptr) {
  cuuint64_t dims[2] = {(cuuint64_t)DM, (cuuint64_t)SEQ}, strides[1] = {(cuuint64_t)DM * 2};
  cuuint32_t box[2] = {80, 64}, es[2] = {1, 1};
  enc(m, CU_TENSOR_MAP_DATA_TYPE_BFLOAT16, 2, ptr, dims, strides, box, es, CU_TENSOR_MAP_INTERLEAVE_NONE, CU_TENSOR_MAP_SWIZZLE_NONE,
      CU_TENSOR_MAP_L2_PROMOTION_NONE, CU_TENSOR_MAP_FLOAT_OOB_FILL_NONE);
}
static void make_b(EncodeFn enc, CUtensorMap* m, const void* ptr, int K, int N, int BN, int bk, int bw) {
  cuuint64_t dims[3] = {(cuuint64_t)BN, (cuuint64_t)(N / BN), (cuuint64_t)K}, strides[2] = {(cuuint64_t)BN * 2, (cuuint64_t)N * 2};
  cuuint32_t box[3] = {(cuuint32_t)bw, 1, (cuuint32_t)bk}, es[3] = {1, 1, 1};
  enc(m, CU_TENSOR_MAP_DATA_TYPE_BFLOAT16, 3, (void*)ptr, dims, strides, box, es, CU_TENSOR_MAP_INTERLEAVE_NONE, bw == 64 ? CU_TENSOR_MAP_SWIZZLE_128B : CU_TENSOR_MAP_SWIZZLE_32B,
      CU_TENSOR_MAP_L2_PROMOTION_NONE, CU_TENSOR_MAP_FLOAT_OOB_FILL_NONE);
}
template <typename... KArgs, typename... Args>
static void launch(void (*kern)(KArgs...), int grid, int threads, int smem, bool pdl, Args... args) {
  cudaFuncSetAttribute(kern, cudaFuncAttributeMaxDynamicSharedMemorySize, smem);
  cudaLaunchConfig_t cfg = {};
  cfg.gridDim = dim3(grid); cfg.blockDim = dim3(threads); cfg.dynamicSmemBytes = smem; cfg.stream = cudaStreamPerThread;
  cudaLaunchAttribute at[1];
  at[0].id = cudaLaunchAttributeProgrammaticStreamSerialization; at[0].val.programmaticStreamSerializationAllowed = 1;
  cfg.attrs = at; cfg.numAttrs = pdl ? 1 : 0;
  cudaLaunchKernelEx(&cfg, kern, KArgs(args)...);
}

static void make_pref(signed char* pref, int ntpc) {
  auto kern = chain_kernel<PH_WO | PH_W1 | PH_W2, false, true>;
  cudaFuncSetAttribute(kern, cudaFuncAttributeMaxDynamicSharedMemorySize, CHAIN_SMEM);
  cudaFuncSetAttribute(kern, cudaFuncAttributeNonPortableClusterSizeAllowed, 1);
  int n[10] = {0};
  for (int t = 2; t <= 8; t++) {
    cudaLaunchConfig_t cfg = {};
    cfg.gridDim = dim3(2 * t * 16); cfg.blockDim = dim3(CHAIN_THREADS); cfg.dynamicSmemBytes = CHAIN_SMEM;
    cudaLaunchAttribute at[1];
    at[0].id = cudaLaunchAttributeClusterDimension; at[0].val.clusterDim.x = 2 * t; at[0].val.clusterDim.y = 1; at[0].val.clusterDim.z = 1;
    cfg.attrs = at; cfg.numAttrs = 1;
    if (cudaOccupancyMaxActiveClusters(&n[t], kern, &cfg) != cudaSuccess) { n[t] = -1; cudaGetLastError(); }
  }
  int best[10] = {0}, cnt[10], found = 0;
  for (int code = 0; code < 1000000 && !found; code++) {
    int c = code, tot = 0, g = 0;
    for (int m = 0; m < 10; m++) cnt[m] = 0;
    for (int m = 4; m <= 9; m++) { cnt[m] = c % 10; c /= 10; tot += cnt[m] * m; g += cnt[m]; }
    if (g > 9 || tot > ntpc) continue;
    bool ok = true;
    for (int t = 3; t <= 8 && ok; t++) { int s = 0; for (int m = 4; m <= 9; m++) s += cnt[m] * (m / t); ok = (s == n[t]); }
    if (ok) { found = 1; for (int m = 0; m < 10; m++) best[m] = cnt[m]; }
  }
  int grp[80], size[10], ng = 0, id = 0;
  for (int t = 0; t < 80; t++) { grp[t] = -1; pref[2 * t] = pref[2 * t + 1] = -1; }
  if (found) {
    for (int m = 4; m <= 9; m++) for (int k = 0; k < best[m]; k++) size[ng++] = m;
    for (int r = 0; r < 9; r++) for (int g = 0; g < ng; g++) if (size[g] > r && id < ntpc) grp[id++] = g;
  }
  int nb = 0;
  bool used[80] = {false};
  auto put = [&](int t, int blk, int w) {
    const int tile = blk * 16 + w * 2;
    pref[2 * t] = (signed char)tile; pref[2 * t + 1] = (signed char)(tile + 1); used[t] = true;
  };
  for (int g = 0; g < ng && nb < 8; g++)
    if (size[g] >= 8) {
      int w = 0;
      for (int t = 0; t < ntpc && w < 8; t++) if (grp[t] == g) put(t, nb, w++);
      nb++;
    }
  int pos = nb * 8;
  for (int pass = 0; pass < 2; pass++)
    for (int g = 0; g <= ng; g++)
      for (int t = 0; t < ntpc && pos < 64; t++)
        if (!used[t] && (g < ng ? (grp[t] == g && (size[g] < 8) == (pass == 0)) : (pass == 1 && grp[t] < 0))) { put(t, pos >> 3, pos & 7); pos++; }
}

extern "C" void kernel_launch(void* const* d_in, const int* in_sizes, int n_in, void* d_out, int out_size) {
  const bf16* x = (const bf16*)d_in[0];
  const bf16* wqkv = (const bf16*)d_in[1];
  const bf16* wo = (const bf16*)d_in[2];
  const bf16* w1 = (const bf16*)d_in[4];
  const bf16* b1 = (const bf16*)d_in[5];
  const bf16* w2 = (const bf16*)d_in[6];
  const bf16* b2 = (const bf16*)d_in[7];
  void* fn = nullptr;
  cudaDriverEntryPointQueryResult qr;
  cudaGetDriverEntryPoint("cuTensorMapEncodeTiled", &fn, cudaEnableDefault, &qr);
  EncodeFn enc = (EncodeFn)fn;
  void *px0, *px2, *pf, *pz;
  cudaGetSymbolAddress(&px0, g_x0);
  cudaGetSymbolAddress(&px2, g_x2); cudaGetSymbolAddress(&pf, g_s);
  unsigned int* flags = ((Small*)pf)->flags;
  pz = ((Small*)pf)->zeros;

  int nsm = 132;
  cudaDeviceGetAttribute(&nsm, cudaDevAttrMultiProcessorCount, 0);
  const int ngrid = nsm >= 128 ? (nsm > 160 ? 160 : (nsm & ~1)) : 128;
  ChainParams p;
  make_pref(p.pref, ngrid / 2);
  make_a(enc, &p.a_x, x, DM);
  make_out(enc, &p.o_out, d_out);
  AttParams ap;
  make_b(enc, &p.b_wo, wo, DM, DM, 80, 64, 16); make_b(enc, &p.b_w1, w1, DM, FF, 216, 64, 16); make_b(enc, &ap.b_w2, w2, FF, DM, 80, 96, 16);
  ap.zeros = (const uint32_t*)pz;
  make_b(enc, &p.b_wqkv, wqkv, DM, 1920, 120, 64, 64);
  p.xres = (const bf16*)px0; p.xin = x; p.b1 = b1; p.b2 = b2; p.flags = flags;

  launch(chain_kernel<PH_QKV, true, false>, ngrid, CHAIN_THREADS, CHAIN_SMEM, false, p);
  ap.norms = flags + NORM_OFF; ap.reset_a = flags; ap.reset_b = flags + FLAG_SET + NORM_OFF; ap.reset_c = flags + 2 * FLAG_SET; ap.jobs = 1;
  launch(att_kernel, 128, 512, ATT_SMEM, true, ap);
  p.flags = flags + FLAG_SET;
  launch(chain_kernel<PH_WO | PH_W1 | PH_W2 | PH_QKV, false, false>, ngrid, CHAIN_THREADS, CHAIN_SMEM, true, p);
  ap.norms = flags + FLAG_SET + NORM_OFF; ap.reset_a = flags + FLAG_SET; ap.reset_b = flags + NORM_OFF; ap.reset_c = nullptr; ap.jobs = 0;
  launch(att_kernel, 128, 512, ATT_SMEM, true, ap);
  p.xres = (const bf16*)px2; p.flags = flags + 2 * FLAG_SET;
  launch(chain_kernel<PH_WO | PH_W1 | PH_W2, false, true>, ngrid, CHAIN_THREADS, CHAIN_SMEM, true, p);
}
```

```cpp
#include <cuda_runtime.h>
#include <cuda_bf16.h>
#include <cuda.h>
#include <stdint.h>

typedef __nv_bfloat16 bf16;

constexpr int SEQ = 2048, DM = 640, FF = 1728;
constexpr float LN_EPS = 1e-5f;
constexpr int HEAD_BYTES = 98304;
constexpr uint32_t MUFU_MASK = 0x1259u;
__host__ __device__ constexpr bool is_mufu(int g) { return (MUFU_MASK >> (g & 15)) & 1u; }

__device__ __align__(1024) bf16 g_qkv[96 * (HEAD_BYTES / 2)];
constexpr int WT_WO = 0, WT_W1 = WT_WO + 80 * 10240, WT_W2 = WT_W1 + 160 * 14336, WT_QKV = WT_W2 + 144 * 15360, WT_END = WT_QKV + 160 * 16384;
__device__ __align__(1024) uint8_t g_wt[WT_END];
__device__ __forceinline__ int x_line(int row, int cg) { return (((row >> 7) * 10 + (cg >> 3)) * 16 + ((row >> 3) & 15)) * 8 + (cg & 7); }
__device__ __forceinline__ int o_line(int row, int cg) { return (((row >> 6) * 10 + (cg >> 3)) * 8 + ((row >> 3) & 7)) * 8 + (cg & 7); }
__device__ __forceinline__ int h_line(int row, int cg) { return (((row >> 6) * 18 + cg / 12) * 8 + ((row >> 3) & 7)) * 12 + cg % 12; }
__device__ __align__(1024) bf16 g_x0[SEQ * DM];
__device__ __align__(1024) bf16 g_o[SEQ * DM];
__device__ __align__(1024) bf16 g_x1[SEQ * DM];
__device__ __align__(1024) bf16 g_x2[SEQ * DM];
__device__ __align__(1024) bf16 g_h[SEQ * FF];
constexpr int FLAG_SET = 320, NORM_OFF = 256;
struct Small {
  float2 st0[2 * SEQ];
  float2 st1[8 * SEQ];
  float2 st2[8 * SEQ];
  float csp_w1[10 * 1792];
  float cs_qkv[1920];
  unsigned int flags[3 * FLAG_SET];
  uint32_t zeros[4];
};
__device__ __align__(1024) Small g_s;

__device__ __forceinline__ uint32_t smem_u32(const void* p) { return (uint32_t)__cvta_generic_to_shared(p); }
__device__ __forceinline__ void mbar_init(uint32_t bar, int cnt) { asm volatile("mbarrier.init.shared::cta.b64 [%0], %1;" ::"r"(bar), "r"(cnt) : "memory"); }
__device__ __forceinline__ void mbar_expect_tx(uint32_t bar, uint32_t bytes) { asm volatile("mbarrier.arrive.expect_tx.shared::cta.b64 _, [%0], %1;" ::"r"(bar), "r"(bytes) : "memory"); }
__device__ __forceinline__ void mbar_arrive(uint32_t bar) { asm volatile("mbarrier.arrive.shared::cta.b64 _, [%0];" ::"r"(bar) : "memory"); }
__device__ __forceinline__ void mbar_arrive_if(uint32_t bar, bool c) {
  asm volatile("{\n.reg .pred p;\nsetp.ne.u32 p, %1, 0;\n@p mbarrier.arrive.shared::cta.b64 _, [%0];\n}\n" ::"r"(bar), "r"((uint32_t)c) : "memory");
}
__device__ __forceinline__ bool mbar_try(uint32_t bar, uint32_t parity) {
  uint32_t ok;
  asm volatile("{\n.reg .pred p;\nmbarrier.try_wait.parity.shared::cta.b64 p, [%1], %2;\nselp.u32 %0, 1, 0, p;\n}\n" : "=r"(ok) : "r"(bar), "r"(parity) : "memory");
  return ok != 0;
}
__device__ __forceinline__ bool mbar_test(uint32_t bar, uint32_t parity) {
  uint32_t ok;
  asm volatile("{\n.reg .pred p;\nmbarrier.test_wait.parity.shared::cta.b64 p, [%1], %2;\nselp.u32 %0, 1, 0, p;\n}\n" : "=r"(ok) : "r"(bar), "r"(parity) : "memory");
  return ok != 0;
}
__device__ __forceinline__ void mbar_wait(uint32_t bar, uint32_t parity) {
  if (mbar_try(bar, parity)) return;
#pragma unroll 1
  for (int it = 0; it < (1 << 22); it++)
    if (mbar_try(bar, parity)) return;
  __trap();
}
__device__ __forceinline__ void mbar_wait_warp(uint32_t bar, uint32_t parity) {
#pragma unroll 1
  for (int it = 0; !__all_sync(0xffffffffu, mbar_try(bar, parity)); it++)
    if (it > (1 << 22)) __trap();
}
__device__ __forceinline__ void flag_wait(const unsigned int* f, unsigned int target) {
  unsigned int v;
#pragma unroll 1
  for (int it = 0; it < (1 << 22); it++) {
    asm volatile("ld.acquire.gpu.global.u32 %0, [%1];" : "=r"(v) : "l"(f) : "memory");
    if (v >= target) return;
  }
  __trap();
}
__device__ __forceinline__ void flag_signal(unsigned int* f) { asm volatile("red.release.gpu.global.add.u32 [%0], 1;" ::"l"(f) : "memory"); }
__device__ __forceinline__ void fence_async_global() { asm volatile("fence.proxy.async.global;" ::: "memory"); }
__device__ __forceinline__ void pdl_wait() { asm volatile("griddepcontrol.wait;" ::: "memory"); }
__device__ __forceinline__ void pdl_launch() { asm volatile("griddepcontrol.launch_dependents;" ::: "memory"); }
__device__ __forceinline__ void named_bar(int id, int n) { asm volatile("bar.sync %0, %1;" ::"r"(id), "r"(n) : "memory"); }
__device__ __forceinline__ void bulk_g2s(uint32_t dst, const void* src, uint32_t bytes, uint32_t bar) {
  asm volatile("cp.async.bulk.shared::cluster.global.mbarrier::complete_tx::bytes [%0], [%1], %2, [%3];" ::"r"(dst), "l"(src), "r"(bytes), "r"(bar) : "memory");
}
__device__ __forceinline__ void tma_2d(uint32_t dst, const CUtensorMap* m, int c0, int c1, uint32_t bar) {
  asm volatile("cp.async.bulk.tensor.2d.shared::cluster.global.mbarrier::complete_tx::bytes [%0], [%1, {%3, %4}], [%2];" ::"r"(dst), "l"(m), "r"(bar), "r"(c0), "r"(c1) : "memory");
}
__device__ __forceinline__ void tma_3d(uint32_t dst, const CUtensorMap* m, int c0, int c1, int c2, uint32_t bar) {
  asm volatile("cp.async.bulk.tensor.3d.shared::cluster.global.mbarrier::complete_tx::bytes [%0], [%1, {%3, %4, %5}], [%2];" ::"r"(dst), "l"(m), "r"(bar), "r"(c0), "r"(c1), "r"(c2) : "memory");
}
__device__ __forceinline__ void prefetch_map(const CUtensorMap* m) { asm volatile("prefetch.tensormap [%0];" ::"l"(m) : "memory"); }
__device__ __forceinline__ void wg_fence() { asm volatile("wgmma.fence.sync.aligned;" ::: "memory"); }
__device__ __forceinline__ void wg_commit() { asm volatile("wgmma.commit_group.sync.aligned;" ::: "memory"); }
template <int N> __device__ __forceinline__ void wg_wait() { asm volatile("wgmma.wait_group.sync.aligned %0;" ::"n"(N) : "memory"); }
template <int N> __device__ __forceinline__ void fence_regs(float (&d)[N]) {
#pragma unroll
  for (int i = 0; i < N; i++) asm volatile("" : "+f"(d[i])::"memory");
}
template <int N> __device__ __forceinline__ void fence_regs(uint32_t (&d)[N]) {
#pragma unroll
  for (int i = 0; i < N; i++) asm volatile("" : "+r"(d[i])::"memory");
}
__device__ __forceinline__ uint64_t mk_desc(uint32_t addr, uint32_t lbo, uint32_t sbo, uint64_t swz) {
  return (uint64_t)((addr & 0x3FFFF) >> 4) | ((uint64_t)(lbo >> 4) << 16) | ((uint64_t)(sbo >> 4) << 32) | (swz << 62);
}
__device__ __forceinline__ uint32_t pack_bf16(float lo, float hi) {
  uint32_t r;
  asm("cvt.rn.bf16x2.f32 %0, %1, %2;" : "=r"(r) : "f"(hi), "f"(lo));
  return r;
}
__device__ __forceinline__ float bf_lo(uint32_t v) { return __uint_as_float(v << 16); }
__device__ __forceinline__ float bf_hi(uint32_t v) { return __uint_as_float(v & 0xFFFF0000u); }
__device__ __forceinline__ float ex2(float x) { float r; asm("ex2.approx.ftz.f32 %0, %1;" : "=f"(r) : "f"(x)); return r; }

template<int TB> __device__ __forceinline__ void wgmma_rs_n24(float (&d)[12], uint32_t a0, uint32_t a1, uint32_t a2, uint32_t a3, uint64_t db, int sd) {
  asm volatile("{\n.reg .pred p;\nsetp.ne.b32 p, %17, 0;\n"
    "wgmma.mma_async.sync.aligned.m64n24k16.f32.bf16.bf16 "
    "{%0,%1,%2,%3,%4,%5,%6,%7,%8,%9,%10,%11}, "
    "{%12,%13,%14,%15}, %16, p, 1, 1, %18;\n}\n"
    : "+f"(d[0]),"+f"(d[1]),"+f"(d[2]),"+f"(d[3]),"+f"(d[4]),"+f"(d[5]),"+f"(d[6]),"+f"(d[7]),"+f"(d[8]),"+f"(d[9]),"+f"(d[10]),"+f"(d[11])
    : "r"(a0), "r"(a1), "r"(a2), "r"(a3), "l"(db), "r"(sd), "n"(TB));
}
template<int TB> __device__ __forceinline__ void wgmma_rs_n120(float (&d)[60], uint32_t a0, uint32_t a1, uint32_t a2, uint32_t a3, uint64_t db, int sd) {
  asm volatile("{\n.reg .pred p;\nsetp.ne.b32 p, %65, 0;\n"
    "wgmma.mma_async.sync.aligned.m64n120k16.f32.bf16.bf16 "
    "{%0,%1,%2,%3,%4,%5,%6,%7,%8,%9,%10,%11,%12,%13,%14,%15,%16,%17,%18,%19,%20,%21,%22,%23,%24,%25,%26,%27,%28,%29,%30,%31,%32,%33,%34,%35,%36,%37,%38,%39,%40,%41,%42,%43,%44,%45,%46,%47,%48,%49,%50,%51,%52,%53,%54,%55,%56,%57,%58,%59}, "
    "{%60,%61,%62,%63}, %64, p, 1, 1, %66;\n}\n"
    : "+f"(d[0]),"+f"(d[1]),"+f"(d[2]),"+f"(d[3]),"+f"(d[4]),"+f"(d[5]),"+f"(d[6]),"+f"(d[7]),"+f"(d[8]),"+f"(d[9]),"+f"(d[10]),"+f"(d[11]),"+f"(d[12]),"+f"(d[13]),"+f"(d[14]),"+f"(d[15]),"+f"(d[16]),"+f"(d[17]),"+f"(d[18]),"+f"(d[19]),"+f"(d[20]),"+f"(d[21]),"+f"(d[22]),"+f"(d[23]),"+f"(d[24]),"+f"(d[25]),"+f"(d[26]),"+f"(d[27]),"+f"(d[28]),"+f"(d[29]),"+f"(d[30]),"+f"(d[31]),"+f"(d[32]),"+f"(d[33]),"+f"(d[34]),"+f"(d[35]),"+f"(d[36]),"+f"(d[37]),"+f"(d[38]),"+f"(d[39]),"+f"(d[40]),"+f"(d[41]),"+f"(d[42]),"+f"(d[43]),"+f"(d[44]),"+f"(d[45]),"+f"(d[46]),"+f"(d[47]),"+f"(d[48]),"+f"(d[49]),"+f"(d[50]),"+f"(d[51]),"+f"(d[52]),"+f"(d[53]),"+f"(d[54]),"+f"(d[55]),"+f"(d[56]),"+f"(d[57]),"+f"(d[58]),"+f"(d[59])
    : "r"(a0), "r"(a1), "r"(a2), "r"(a3), "l"(db), "r"(sd), "n"(TB));
}
template<int TB> __device__ __forceinline__ void wgmma_rs_n128(float (&d)[64], uint32_t a0, uint32_t a1, uint32_t a2, uint32_t a3, uint64_t db, int sd) {
  asm volatile("{\n.reg .pred p;\nsetp.ne.b32 p, %69, 0;\n"
    "wgmma.mma_async.sync.aligned.m64n128k16.f32.bf16.bf16 "
    "{%0,%1,%2,%3,%4,%5,%6,%7,%8,%9,%10,%11,%12,%13,%14,%15,%16,%17,%18,%19,%20,%21,%22,%23,%24,%25,%26,%27,%28,%29,%30,%31,%32,%33,%34,%35,%36,%37,%38,%39,%40,%41,%42,%43,%44,%45,%46,%47,%48,%49,%50,%51,%52,%53,%54,%55,%56,%57,%58,%59,%60,%61,%62,%63}, "
    "{%64,%65,%66,%67}, %68, p, 1, 1, %70;\n}\n"
    : "+f"(d[0]),"+f"(d[1]),"+f"(d[2]),"+f"(d[3]),"+f"(d[4]),"+f"(d[5]),"+f"(d[6]),"+f"(d[7]),"+f"(d[8]),"+f"(d[9]),"+f"(d[10]),"+f"(d[11]),"+f"(d[12]),"+f"(d[13]),"+f"(d[14]),"+f"(d[15]),"+f"(d[16]),"+f"(d[17]),"+f"(d[18]),"+f"(d[19]),"+f"(d[20]),"+f"(d[21]),"+f"(d[22]),"+f"(d[23]),"+f"(d[24]),"+f"(d[25]),"+f"(d[26]),"+f"(d[27]),"+f"(d[28]),"+f"(d[29]),"+f"(d[30]),"+f"(d[31]),"+f"(d[32]),"+f"(d[33]),"+f"(d[34]),"+f"(d[35]),"+f"(d[36]),"+f"(d[37]),"+f"(d[38]),"+f"(d[39]),"+f"(d[40]),"+f"(d[41]),"+f"(d[42]),"+f"(d[43]),"+f"(d[44]),"+f"(d[45]),"+f"(d[46]),"+f"(d[47]),"+f"(d[48]),"+f"(d[49]),"+f"(d[50]),"+f"(d[51]),"+f"(d[52]),"+f"(d[53]),"+f"(d[54]),"+f"(d[55]),"+f"(d[56]),"+f"(d[57]),"+f"(d[58]),"+f"(d[59]),"+f"(d[60]),"+f"(d[61]),"+f"(d[62]),"+f"(d[63])
    : "r"(a0), "r"(a1), "r"(a2), "r"(a3), "l"(db), "r"(sd), "n"(TB));
}
__device__ __forceinline__ void wgmma_ss(float (&d)[40], uint64_t da, uint64_t db, int sd) {
  asm volatile("{\n.reg .pred p;\nsetp.ne.b32 p, %42, 0;\n"
    "wgmma.mma_async.sync.aligned.m64n80k16.f32.bf16.bf16 "
    "{%0,%1,%2,%3,%4,%5,%6,%7,%8,%9,%10,%11,%12,%13,%14,%15,%16,%17,%18,%19,%20,%21,%22,%23,%24,%25,%26,%27,%28,%29,%30,%31,%32,%33,%34,%35,%36,%37,%38,%39}, "
    "%40, %41, p, 1, 1, 0, 1;\n}\n"
    : "+f"(d[0]),"+f"(d[1]),"+f"(d[2]),"+f"(d[3]),"+f"(d[4]),"+f"(d[5]),"+f"(d[6]),"+f"(d[7]),"+f"(d[8]),"+f"(d[9]),"+f"(d[10]),"+f"(d[11]),"+f"(d[12]),"+f"(d[13]),"+f"(d[14]),"+f"(d[15]),"+f"(d[16]),"+f"(d[17]),"+f"(d[18]),"+f"(d[19]),"+f"(d[20]),"+f"(d[21]),"+f"(d[22]),"+f"(d[23]),"+f"(d[24]),"+f"(d[25]),"+f"(d[26]),"+f"(d[27]),"+f"(d[28]),"+f"(d[29]),"+f"(d[30]),"+f"(d[31]),"+f"(d[32]),"+f"(d[33]),"+f"(d[34]),"+f"(d[35]),"+f"(d[36]),"+f"(d[37]),"+f"(d[38]),"+f"(d[39])
    : "l"(da), "l"(db), "r"(sd));
}
__device__ __forceinline__ void wgmma_ss(float (&d)[56], uint64_t da, uint64_t db, int sd) {
  asm volatile("{\n.reg .pred p;\nsetp.ne.b32 p, %58, 0;\n"
    "wgmma.mma_async.sync.aligned.m64n112k16.f32.bf16.bf16 "
    "{%0,%1,%2,%3,%4,%5,%6,%7,%8,%9,%10,%11,%12,%13,%14,%15,%16,%17,%18,%19,%20,%21,%22,%23,%24,%25,%26,%27,%28,%29,%30,%31,%32,%33,%34,%35,%36,%37,%38,%39,%40,%41,%42,%43,%44,%45,%46,%47,%48,%49,%50,%51,%52,%53,%54,%55}, "
    "%56, %57, p, 1, 1, 0, 1;\n}\n"
    : "+f"(d[0]),"+f"(d[1]),"+f"(d[2]),"+f"(d[3]),"+f"(d[4]),"+f"(d[5]),"+f"(d[6]),"+f"(d[7]),"+f"(d[8]),"+f"(d[9]),"+f"(d[10]),"+f"(d[11]),"+f"(d[12]),"+f"(d[13]),"+f"(d[14]),"+f"(d[15]),"+f"(d[16]),"+f"(d[17]),"+f"(d[18]),"+f"(d[19]),"+f"(d[20]),"+f"(d[21]),"+f"(d[22]),"+f"(d[23]),"+f"(d[24]),"+f"(d[25]),"+f"(d[26]),"+f"(d[27]),"+f"(d[28]),"+f"(d[29]),"+f"(d[30]),"+f"(d[31]),"+f"(d[32]),"+f"(d[33]),"+f"(d[34]),"+f"(d[35]),"+f"(d[36]),"+f"(d[37]),"+f"(d[38]),"+f"(d[39]),"+f"(d[40]),"+f"(d[41]),"+f"(d[42]),"+f"(d[43]),"+f"(d[44]),"+f"(d[45]),"+f"(d[46]),"+f"(d[47]),"+f"(d[48]),"+f"(d[49]),"+f"(d[50]),"+f"(d[51]),"+f"(d[52]),"+f"(d[53]),"+f"(d[54]),"+f"(d[55])
    : "l"(da), "l"(db), "r"(sd));
}
__device__ __forceinline__ void wgmma_ss(float (&d)[60], uint64_t da, uint64_t db, int sd) {
  asm volatile("{\n.reg .pred p;\nsetp.ne.b32 p, %62, 0;\n"
    "wgmma.mma_async.sync.aligned.m64n120k16.f32.bf16.bf16 "
    "{%0,%1,%2,%3,%4,%5,%6,%7,%8,%9,%10,%11,%12,%13,%14,%15,%16,%17,%18,%19,%20,%21,%22,%23,%24,%25,%26,%27,%28,%29,%30,%31,%32,%33,%34,%35,%36,%37,%38,%39,%40,%41,%42,%43,%44,%45,%46,%47,%48,%49,%50,%51,%52,%53,%54,%55,%56,%57,%58,%59}, "
    "%60, %61, p, 1, 1, 0, 1;\n}\n"
    : "+f"(d[0]),"+f"(d[1]),"+f"(d[2]),"+f"(d[3]),"+f"(d[4]),"+f"(d[5]),"+f"(d[6]),"+f"(d[7]),"+f"(d[8]),"+f"(d[9]),"+f"(d[10]),"+f"(d[11]),"+f"(d[12]),"+f"(d[13]),"+f"(d[14]),"+f"(d[15]),"+f"(d[16]),"+f"(d[17]),"+f"(d[18]),"+f"(d[19]),"+f"(d[20]),"+f"(d[21]),"+f"(d[22]),"+f"(d[23]),"+f"(d[24]),"+f"(d[25]),"+f"(d[26]),"+f"(d[27]),"+f"(d[28]),"+f"(d[29]),"+f"(d[30]),"+f"(d[31]),"+f"(d[32]),"+f"(d[33]),"+f"(d[34]),"+f"(d[35]),"+f"(d[36]),"+f"(d[37]),"+f"(d[38]),"+f"(d[39]),"+f"(d[40]),"+f"(d[41]),"+f"(d[42]),"+f"(d[43]),"+f"(d[44]),"+f"(d[45]),"+f"(d[46]),"+f"(d[47]),"+f"(d[48]),"+f"(d[49]),"+f"(d[50]),"+f"(d[51]),"+f"(d[52]),"+f"(d[53]),"+f"(d[54]),"+f"(d[55]),"+f"(d[56]),"+f"(d[57]),"+f"(d[58]),"+f"(d[59])
    : "l"(da), "l"(db), "r"(sd));
}


constexpr int PH_WO = 1, PH_W1 = 2, PH_W2 = 4, PH_QKV = 8;
constexpr int SA = 4, SB = 10, STAGE = 16384;
constexpr int SM_B = SA * STAGE;
constexpr int SM_CS = SM_B + SB * STAGE;
constexpr int SM_B1 = SM_CS + 448;
constexpr int SM_ROW = SM_B1 + 224;
constexpr int SM_BAR = SM_ROW + 2048;
constexpr int CHAIN_SMEM = SM_BAR + 344;
static_assert(CHAIN_SMEM <= 232448, "shared memory");
constexpr int CHAIN_THREADS = 352;
constexpr int BAR_FA = 0, BAR_EA = SA * 8, BAR_FB = 2 * SA * 8, BAR_EB = (2 * SA + SB) * 8, BAR_AUX = (2 * SA + 2 * SB) * 8, BAR_JOB = BAR_AUX + 32,
              BAR_FH = BAR_JOB, BAR_EH = BAR_JOB + 40, BAR_TILE = BAR_JOB + 80;

struct alignas(64) ChainParams {
  CUtensorMap a_x, b_wo, b_w1, b_wqkv, o_out;
  const bf16* xres;
  const bf16* xin;
  const bf16 *b1, *b2;
  unsigned int* flags;
  signed char pref[160];
};

template <int V> struct IC { static constexpr int value = V; };
struct Ring { uint32_t s, ph; };
template <int N> __device__ __forceinline__ void ring_adv(Ring& r) { if (++r.s == N) { r.s = 0; r.ph ^= 1; } }

template <int N, int STRIDE>
__device__ __forceinline__ void produce(int n, uint32_t bytes, uint32_t lim, const uint8_t* src, uint32_t dst, uint32_t full, uint32_t empty, Ring& r) {
#pragma unroll 1
  for (int kt = 0; kt < n; kt++) {
    if (lim) mbar_wait(full + (r.s >= lim ? r.s - lim : r.s + N - lim) * 8, r.s >= lim ? r.ph : r.ph ^ 1);
    mbar_wait(empty + r.s * 8, r.ph ^ 1);
    mbar_expect_tx(full + r.s * 8, bytes);
    bulk_g2s(dst + r.s * STRIDE, src + kt * bytes, bytes, full + r.s * 8);
    ring_adv<N>(r);
  }
}
__device__ __forceinline__ void bulk_s2g(void* dst, uint32_t src, uint32_t bytes) {
  asm volatile("cp.async.bulk.global.shared::cta.bulk_group [%0], [%1], %2;\ncp.async.bulk.commit_group;" ::"l"(dst), "r"(src), "r"(bytes) : "memory");
}
template <int BK, bool B128> __device__ __forceinline__ uint64_t b_desc(uint32_t addr) { return B128 ? mk_desc(addr, 8192, 1024, 1) : mk_desc(addr, BK * 32, 256, 3); }

template <int BN, int MT, int BK, int APT, bool TILED, bool B128, bool HR = false>
__device__ __forceinline__ void mainloop(float (&acc)[MT][BN / 2], uint32_t sbase, uint32_t bars, int lane, int wg, int KT, int a0, bool pass, Ring& rb, int cont = 0) {
  constexpr int NA = HR ? 5 : SA, AST = HR ? 12288 : STAGE, FA = HR ? BAR_FH : BAR_FA, EA = HR ? BAR_EH : BAR_EA;
  Ring ra{(uint32_t)a0 % NA, ((uint32_t)a0 / NA) & 1};
#pragma unroll
  for (int m = 0; m < MT; m++) fence_regs(acc[m]);
  if (HR || a0 != 0) named_bar(6 - wg, 256);
  mbar_wait(bars + BAR_FB + rb.s * 8, rb.ph);
  mbar_wait(bars + FA + ra.s * 8, ra.ph);
  const uint64_t da0 = TILED ? mk_desc(sbase, 128, BK * 16, 0) : mk_desc(sbase, 16, 1024, 1), db0 = b_desc<BK, B128>(sbase + SM_B);
  constexpr int NS = BK / 16, H = MT == 2 ? 1 : 2, KA = TILED ? 16 : 2, KB = B128 ? 128 : 32;
  uint32_t relA = 0, relB = 0;
  uint64_t da = da0 + ra.s * (AST / 16), db = db0 + rb.s * (STAGE / 16);
  auto part = [&](auto k0, auto k1, int sd) {
#pragma unroll
    for (int k = k0.value; k < k1.value; k++)
#pragma unroll
      for (int m = 0; m < MT; m++) wgmma_ss(acc[m], da + m * 512 + k * KA, db + k * KB, k == 0 ? sd : 1);
    wg_commit();
  };
  wg_fence();
  part(IC<0>{}, IC<H>{}, cont);
#pragma unroll 1
  for (int kt = 0; kt < KT - 1; kt++) {
    const bool adv = APT == 1 || (kt & 1);
    const uint32_t curA = adv ? bars + EA + ra.s * 8 : 0, curB = bars + BAR_EB + rb.s * 8;
    if (adv) ring_adv<NA>(ra);
    ring_adv<SB>(rb);
    const uint64_t na = adv ? da0 + ra.s * (AST / 16) : da + 512, nb = db0 + rb.s * (STAGE / 16);
    const bool ok = mbar_test(bars + BAR_FB + rb.s * 8, rb.ph) & mbar_test(bars + FA + ra.s * 8, ra.ph);
    wg_wait<1>();
    mbar_arrive_if(relA, lane == 0 && relA);
    mbar_arrive_if(relB, lane == 0 && relB);
    wg_fence();
    part(IC<H>{}, IC<NS>{}, 1);
    relA = curA; relB = curB; da = na; db = nb;
    if (!ok) { mbar_wait(bars + BAR_FB + rb.s * 8, rb.ph); mbar_wait(bars + FA + ra.s * 8, ra.ph); }
    wg_fence();
    part(IC<0>{}, IC<H>{}, 1);
  }
  if (pass) asm volatile("bar.arrive %0, 256;" ::"r"(5 + wg) : "memory");
  wg_wait<1>();
  mbar_arrive_if(relA, lane == 0 && relA);
  mbar_arrive_if(relB, lane == 0);
  wg_fence();
  part(IC<H>{}, IC<NS>{}, 1);
  relA = bars + EA + ra.s * 8; relB = bars + BAR_EB + rb.s * 8;
  ring_adv<SB>(rb);
  wg_wait<0>();
#pragma unroll
  for (int m = 0; m < MT; m++) fence_regs(acc[m]);
  if (lane == 0) { mbar_arrive(relA); mbar_arrive(relB); }
}
__device__ __forceinline__ void acquire_stage(uint32_t bars, const Ring& rb, uint32_t s) { mbar_wait(bars + BAR_EB + s * 8, s >= rb.s ? rb.ph ^ 1 : rb.ph); }

template <bool FINAL>
__device__ __forceinline__ void epi_resid(const float (&acc)[40], uint32_t (&res)[20], bf16* out, float2* st, uint8_t* stage, int row0, int j, int lane) {
  const int q = lane & 3;
  uint32_t* o0 = FINAL ? (uint32_t*)(stage + (row0 & 63) * 160) + q : (uint32_t*)out + lane;
  float s0 = 0.f, t0 = 0.f, s1 = 0.f, t1 = 0.f;
#pragma unroll
  for (int b = 0; b < 10; b++) {
    res[2 * b] = pack_bf16(acc[4 * b], acc[4 * b + 1]);
    res[2 * b + 1] = pack_bf16(acc[4 * b + 2], acc[4 * b + 3]);
    if (FINAL) { o0[b * 4] = res[2 * b]; o0[b * 4 + 320] = res[2 * b + 1]; }
    else { const int ln = x_line(row0, j * 10 + b); o0[ln * 32] = res[2 * b]; o0[ln * 32 + 256] = res[2 * b + 1]; }
  }
  if (!FINAL) {
#pragma unroll
    for (int b = 0; b < 10; b++) {
      s0 += acc[4 * b] + acc[4 * b + 1]; t0 = fmaf(acc[4 * b], acc[4 * b], fmaf(acc[4 * b + 1], acc[4 * b + 1], t0));
      s1 += acc[4 * b + 2] + acc[4 * b + 3]; t1 = fmaf(acc[4 * b + 2], acc[4 * b + 2], fmaf(acc[4 * b + 3], acc[4 * b + 3], t1));
    }
#pragma unroll
    for (int m = 1; m < 4; m <<= 1) {
      s0 += __shfl_xor_sync(0xffffffffu, s0, m); t0 += __shfl_xor_sync(0xffffffffu, t0, m);
      s1 += __shfl_xor_sync(0xffffffffu, s1, m); t1 += __shfl_xor_sync(0xffffffffu, t1, m);
    }
    if (q < 2) st[j * SEQ + row0 + q * 8] = q ? make_float2(s1, t1) : make_float2(s0, t0);
  }
}
__device__ __forceinline__ void publish(unsigned int* f, int wg, int tid) {
  named_bar(2 + wg, 128);
  if ((tid & 127) == 0) flag_signal(f);
}
__device__ __forceinline__ float gelu_half(float s) {
  const float z = s * fmaf(s * s, 8.f * 0.044715f * 0.7978845608028654f, 2.f * 0.7978845608028654f);
  float th;
  asm("tanh.approx.f32 %0, %1;" : "=f"(th) : "f"(z));
  return fmaf(s, th, s);
}
template <bool DOUBLE> __device__ __forceinline__ float2 row_coef(float s, float t) {
  const float mean = s * (1.f / DM);
  const float var = fmaxf(fmaf(-mean, mean, t * (1.f / DM)), 0.f);
  float r = rsqrtf(var + LN_EPS);
  if (DOUBLE) r *= 0.5f * rsqrtf(var * r * r + LN_EPS);
  return make_float2(r, -r * mean);
}
template <bool DOUBLE, int NP> __device__ __forceinline__ void reduce_stats(const float2* st, float2* dst, int i, int lane) {
  float4 v[2][NP];
#pragma unroll
  for (int rr = 0; rr < 2; rr++)
#pragma unroll
    for (int k = 0; k < NP; k++) v[rr][k] = __ldcg((const float4*)(st + k * SEQ + i * 128 + rr * 64) + lane);
#pragma unroll
  for (int rr = 0; rr < 2; rr++) {
    float s0 = 0.f, t0 = 0.f, s1 = 0.f, t1 = 0.f;
#pragma unroll
    for (int k = 0; k < NP; k++) { s0 += v[rr][k].x; t0 += v[rr][k].y; s1 += v[rr][k].z; t1 += v[rr][k].w; }
    dst[rr * 64 + lane * 2] = row_coef<DOUBLE>(s0, t0);
    dst[rr * 64 + lane * 2 + 1] = row_coef<DOUBLE>(s1, t1);
  }
}

template <int PH, bool FIRST, bool LAST>
__global__ void __launch_bounds__(CHAIN_THREADS, 1) chain_kernel(const __grid_constant__ ChainParams p) {
  extern __shared__ __align__(1024) uint8_t smem[];
  const uint32_t sbase = smem_u32(smem), bars = sbase + SM_BAR;
  float* cs = (float*)(smem + SM_CS);
  uint32_t* sb1 = (uint32_t*)(smem + SM_B1);
  const int tid = threadIdx.x, lane = tid & 31, warp = __shfl_sync(0xffffffffu, tid >> 5, 0);
  if (tid == 32) {
    unsigned int* claim = p.flags + 64;
    uint32_t smid;
    asm volatile("mov.u32 %0, %%smid;" : "=r"(smid));
    int t = smid < 160 ? p.pref[smid] : -1;
    if (t >= 0 && atomicExch(claim + t, 1u) != 0u) t = -2;
    if (t == -1) {
#pragma unroll 1
      for (int it = 0; it < 100000; it++) {
        if (*(volatile unsigned int*)(claim + 128) >= 128u) break;
        __nanosleep(200);
      }
    }
    if (t < 0) {
      t = -1;
      if (*(volatile unsigned int*)(claim + 128) < 128u) {
#pragma unroll 1
        for (int c = 0; c < 128 && t < 0; c++)
          if (atomicExch(claim + c, 1u) == 0u) t = c;
      }
    }
    if (t >= 0) atomicAdd(claim + 128, 1u);
    *(volatile int*)(smem + SM_BAR + BAR_TILE) = t;
  }
  unsigned int* fl = p.flags;
  if (tid == 0) {
    for (int s = 0; s < SA; s++) { mbar_init(bars + BAR_FA + s * 8, 1); mbar_init(bars + BAR_EA + s * 8, 4); }
    for (int s = 0; s < SB; s++) { mbar_init(bars + BAR_FB + s * 8, 1); mbar_init(bars + BAR_EB + s * 8, 8); }
    mbar_init(bars + BAR_AUX, 32); mbar_init(bars + BAR_AUX + 8, 32);
    mbar_init(bars + BAR_AUX + 16, FIRST ? 37 : 32); mbar_init(bars + BAR_AUX + 24, 32);
    for (int s = 0; s < 5; s++) { mbar_init(bars + BAR_FH + s * 8, 1); mbar_init(bars + BAR_EH + s * 8, 4); }
    asm volatile("fence.mbarrier_init.release.cluster;" ::: "memory");
  }
  if (tid == 256) {
    if (FIRST) {
      uint32_t smid;
      asm volatile("mov.u32 %0, %%smid;" : "=r"(smid));
      const int t = smid < 160 ? p.pref[smid] : -1;
      if (t >= 0) {
        asm volatile("cp.async.bulk.prefetch.tensor.2d.L2.global [%0, {%1, %2}];" ::"l"(&p.a_x), "r"(0), "r"((t >> 4) * 256) : "memory");
        asm volatile("cp.async.bulk.prefetch.tensor.3d.L2.global [%0, {%1, %2, %3}];" ::"l"(&p.b_wqkv), "r"(0), "r"(t & 15), "r"(0) : "memory");
        asm volatile("cp.async.bulk.prefetch.tensor.3d.L2.global [%0, {%1, %2, %3}];" ::"l"(&p.b_wqkv), "r"(64), "r"(t & 15), "r"(0) : "memory");
      }
      prefetch_map(&p.b_w1); prefetch_map(&p.b_wo);
    }
    if (LAST) prefetch_map(&p.o_out);
  }
  __syncthreads();
  pdl_launch();
  const int tile = *(volatile int*)(smem + SM_BAR + BAR_TILE);
  if (tile < 0) return;
  const int g = tile >> 4, c = tile & 15;

  if (warp == 9) {
    if (lane == 0) {
      if (FIRST) {
#pragma unroll 1
        for (int kt = 0; kt < 10; kt++) {
          if (kt >= 3) mbar_wait(bars + BAR_FB + (kt - 3) * 8, 0);
          mbar_expect_tx(bars + BAR_FB + kt * 8, STAGE);
          tma_3d(sbase + SM_B + kt * STAGE, &p.b_wqkv, 0, c, kt * 64, bars + BAR_FB + kt * 8);
          tma_3d(sbase + SM_B + kt * STAGE + 8192, &p.b_wqkv, 64, c, kt * 64, bars + BAR_FB + kt * 8);
        }
#pragma unroll 1
        for (int kt = g; kt < 10; kt += 8) {
          mbar_wait(bars + BAR_FB + kt * 8, 0);
          bulk_s2g(g_wt + WT_QKV + (c * 10 + kt) * STAGE, sbase + SM_B + kt * STAGE, STAGE);
        }
        asm volatile("cp.async.bulk.wait_group.read 0;" ::: "memory");
        mbar_arrive(bars + BAR_AUX + 16);
        asm volatile("cp.async.bulk.wait_group 0;" ::: "memory");
      } else {
        Ring r{0, 0};
#pragma unroll 1
        for (int ph = 0; ph < ((PH & PH_QKV) ? 4 : 3); ph++) {
          if (ph == 2) pdl_wait();
          const uint32_t bytes = ph == 0 ? 10240 : (ph == 1 ? 14336 : (ph == 2 ? 15360 : STAGE));
          const int n = ph == 2 ? 18 : 10, off = ph == 0 ? WT_WO : (ph == 1 ? WT_W1 : (ph == 2 ? WT_W2 : WT_QKV));
          produce<SB, STAGE>(n, bytes, ph == 0 ? 0 : (ph == 2 ? 3 : 2), g_wt + off + ((ph & 1) ? c : c >> 1) * n * bytes, sbase + SM_B, bars + BAR_FB,
                             bars + BAR_EB, r);
        }
      }
    }
  } else if (warp == 8) {
    if (lane == 0) {
      Ring r{0, 0};
      if (FIRST) {
#pragma unroll 1
        for (int t = 0; t < 20; t++) {
          mbar_wait(bars + BAR_EA + r.s * 8, r.ph ^ 1);
          mbar_expect_tx(bars + BAR_FA + r.s * 8, STAGE);
          tma_2d(sbase + r.s * STAGE, &p.a_x, (t % 10) * 64, g * 256 + (t / 10) * 128, bars + BAR_FA + r.s * 8);
          ring_adv<SA>(r);
        }
#pragma unroll 1
        for (int job = tile; job < 240; job += 128) {
          const int n = job >> 7;
          mbar_wait(bars + BAR_EB + (3 + n) * 8, 0);
          mbar_expect_tx(bars + BAR_JOB + n * 8, job < 160 ? 14336 : 10240);
#pragma unroll 1
          for (int b = 0; b < (job < 160 ? 7 : 5); b++)
            tma_3d(sbase + SM_B + (3 + n) * STAGE + b * 2048, job < 160 ? &p.b_w1 : &p.b_wo, (job < 160 ? ((job / 10) & 1) * 112 : 0) + b * 16,
                   job < 160 ? job / 20 : job / 10 - 16, (job % 10) * 64, bars + BAR_JOB + n * 8);
        }
#pragma unroll 1
        for (int job = tile; job < 240; job += 128) {
          mbar_wait(bars + BAR_JOB + (job >> 7) * 8, 0);
          bulk_s2g(g_wt + (job < 160 ? WT_W1 + job * 14336 : WT_WO + (job - 160) * 10240), sbase + SM_B + (3 + (job >> 7)) * STAGE, job < 160 ? 14336 : 10240);
        }
        asm volatile("cp.async.bulk.wait_group 0;" ::: "memory");
      } else {
        pdl_wait();
#pragma unroll 1
        for (int ph = 0; ph < ((PH & PH_QKV) ? 3 : 2); ph++) {
#pragma unroll 1
          for (int s = 0; s < 2; s++) {
            if (ph) { flag_wait(fl + (ph - 1) * 32 + g * 2 + s, 16); fence_async_global(); }
            const uint8_t* src = ph == 0 ? (const uint8_t*)g_o + (g * 4 + s * 2 + (c & 1)) * 81920 : (const uint8_t*)(ph == 1 ? g_x1 : g_x2) + (g * 2 + s) * 163840;
            produce<SA, STAGE>(ph ? 10 : 5, 16384, 0, src, sbase, bars + BAR_FA, bars + BAR_EA, r);
          }
          if (ph == 1) {
            Ring rh{0, 0};
#pragma unroll 1
            for (int s = 0; s < SA; s++) mbar_wait(bars + BAR_EA + s * 8, s >= r.s ? r.ph ^ 1 : r.ph);
#pragma unroll 1
            for (int s = 0; s < 4; s++) {
              if (s < 2) { flag_wait(fl + 16 + g * 2 + s, 16); fence_async_global(); }
              produce<5, 12288>(s < 2 ? 10 : 8, 12288, 0, (const uint8_t*)g_h + ((g * 4 + (s & 1) * 2 + (c & 1)) * 18 + (s >> 1) * 10) * 12288, sbase, bars + BAR_FH,
                                bars + BAR_EH, rh);
            }
#pragma unroll 1
            for (int s = 0; s < 5; s++) mbar_wait(bars + BAR_EH + s * 8, s >= rh.s ? rh.ph ^ 1 : rh.ph);
          }
        }
      }
    }
  } else if (warp == 10) {
    float2* srow = (float2*)(smem + SM_ROW);
    if (FIRST) {
      named_bar(4, 160);
      if (lane == 0) flag_signal(fl + g * 2 + (c >> 3));
#pragma unroll 1
      for (int s = 0; s < 2; s++) {
        if (lane == 0) flag_wait(fl + g * 2 + s, 8);
        __syncwarp();
        reduce_stats<false, 2>(g_s.st0, srow + s * 128, g * 2 + s, lane);
        mbar_arrive(bars + BAR_AUX + 16 + s * 8);
      }
#pragma unroll 1
      for (int n = 0; n < 2; n++) {
        const int job = n * 128 + tile;
        if (job < 160) {
          mbar_wait(bars + BAR_JOB + n * 8, 0);
          const uint8_t* base = smem + SM_B + (3 + n) * STAGE + ((lane & 15) >> 1) * 2048 + (lane >> 4) * 1024;
          float a[8];
#pragma unroll
          for (int e = 0; e < 8; e++) a[e] = 0.f;
#pragma unroll 4
          for (int r = 0; r < 32; r++) {
            const uint4 v = *(const uint4*)(base + r * 32 + (((lane & 1) ^ ((r >> 2) & 1)) * 16));
            a[0] += bf_lo(v.x); a[1] += bf_hi(v.x); a[2] += bf_lo(v.y); a[3] += bf_hi(v.y);
            a[4] += bf_lo(v.z); a[5] += bf_hi(v.z); a[6] += bf_lo(v.w); a[7] += bf_hi(v.w);
          }
#pragma unroll
          for (int e = 0; e < 8; e++) a[e] += __shfl_xor_sync(0xffffffffu, a[e], 16);
          if (lane < 14) {
            float4* d = (float4*)(g_s.csp_w1 + (job % 10) * 1792 + (job / 10) * 112 + lane * 8);
            d[0] = make_float4(a[0], a[1], a[2], a[3]); d[1] = make_float4(a[4], a[5], a[6], a[7]);
          }
        }
      }
    } else {
      if (lane < 28) {
        float4 v[10], a = make_float4(0.f, 0.f, 0.f, 0.f);
#pragma unroll
        for (int k = 0; k < 10; k++) v[k] = __ldcg((const float4*)(g_s.csp_w1 + k * 1792 + c * 112) + lane);
#pragma unroll
        for (int k = 0; k < 10; k++) { a.x += v[k].x; a.y += v[k].y; a.z += v[k].z; a.w += v[k].w; }
        ((float4*)cs)[lane] = a;
      }
      for (int k = lane; k < 56; k += 32) {
        const int col = (c >> 1) * 216 + (c & 1) * 112 + k * 2;
        const uint32_t v = col < FF ? __ldg((const uint32_t*)(p.b1 + col)) : 0u;
        sb1[k] = pack_bf16(0.5f * bf_lo(v), 0.5f * bf_hi(v));
      }
#pragma unroll 1
      for (int s = 0; s < 2; s++) {
        if (lane == 0) flag_wait(fl + g * 2 + s, 16);
        __syncwarp();
        reduce_stats<true, 8>(g_s.st1, srow + s * 128, g * 2 + s, lane);
        mbar_arrive(bars + BAR_AUX + s * 8);
      }
      if (PH & PH_QKV) {
        const float4 cq = lane < 30 ? __ldcg((const float4*)(g_s.cs_qkv + c * 120) + lane) : make_float4(0.f, 0.f, 0.f, 0.f);
#pragma unroll 1
        for (int s = 0; s < 2; s++) {
          if (lane == 0) { if (s == 0) flag_wait(fl + 16 + g * 2 + 1, 16); flag_wait(fl + 32 + g * 2 + s, 16); }
          __syncwarp();
          if (s == 0 && lane < 30) ((float4*)cs)[lane] = cq;
          reduce_stats<false, 8>(g_s.st2, srow + s * 128, g * 2 + s, lane);
          mbar_arrive(bars + BAR_AUX + 16 + s * 8);
        }
      }
    }
  } else {
    const int wg = warp >> 2, w4 = warp & 3, q = lane & 3;
    const int rbk = g * 2 + wg, rl = w4 * 16 + (lane >> 2);
    const int rowS = rbk * 128 + (c & 1) * 64 + rl, jS = c >> 1;
    const float2* srow = (const float2*)(smem + SM_ROW) + wg * 128;
    const bool t0 = (tid & 127) == 0;
    Ring rb{0, 0};
    uint32_t res[20];
    if (FIRST) {
      if (wg == 1) {
        const int xrow = g * 256 + c * 16 + (w4 & 1) * 8 + (lane >> 2), xcg = (w4 >> 1) * 40 + q;
        uint4 xv[10];
#pragma unroll
        for (int k = 0; k < 10; k++) xv[k] = __ldg((const uint4*)(p.xin + (size_t)xrow * DM) + xcg + k * 4);
        float xs = 0.f, xt = 0.f;
#pragma unroll
        for (int k = 0; k < 10; k++) {
          const uint32_t e[4] = {xv[k].x, xv[k].y, xv[k].z, xv[k].w};
#pragma unroll
          for (int m = 0; m < 4; m++) { const float a = bf_lo(e[m]), b = bf_hi(e[m]); xs += a + b; xt = fmaf(a, a, fmaf(b, b, xt)); }
        }
#pragma unroll
        for (int m = 1; m < 4; m <<= 1) { xs += __shfl_xor_sync(0xffffffffu, xs, m); xt += __shfl_xor_sync(0xffffffffu, xt, m); }
        if (q == 0) g_s.st0[(w4 >> 1) * SEQ + xrow] = make_float2(xs, xt);
        asm volatile("bar.arrive 4, 160;" ::: "memory");
#pragma unroll
        for (int k = 0; k < 10; k++) *((uint4*)g_x0 + x_line(xrow, xcg + k * 4) * 8 + (xrow & 7)) = xv[k];
        float o[60];
        const uint32_t one = 0x3F803F80u;
#pragma unroll 1
        for (int kt = 0; kt < 10; kt++) {
          mbar_wait(bars + BAR_FB + kt * 8, 0);
          wg_fence();
#pragma unroll
          for (int k = 0; k < 4; k++) wgmma_rs_n120<1>(o, one, one, one, one, b_desc<64, true>(sbase + SM_B + kt * STAGE) + k * 128, (kt | k) != 0);
          wg_commit();
        }
        wg_wait<0>();
        fence_regs(o);
        if ((tid & 127) < 4) {
#pragma unroll
          for (int b = 0; b < 15; b++) {
            *(float2*)(cs + b * 8 + q * 2) = make_float2(o[4 * b], o[4 * b + 1]);
            if (g == 0) *(float2*)(g_s.cs_qkv + c * 120 + b * 8 + q * 2) = make_float2(o[4 * b], o[4 * b + 1]);
          }
          mbar_arrive(bars + BAR_AUX + 16);
        }
        named_bar(3, 128);
      }
    } else {
#pragma unroll
      for (int b = 0; b < 10; b++) {
        const uint32_t* r0 = (const uint32_t*)p.xres + x_line(rowS, jS * 10 + b) * 32 + lane;
        res[2 * b] = __ldcg(r0); res[2 * b + 1] = __ldcg(r0 + 256);
      }
      {
        float acc[1][40];
#pragma unroll
        for (int b = 0; b < 20; b++) { acc[0][2 * b] = bf_lo(res[b]); acc[0][2 * b + 1] = bf_hi(res[b]); }
        mainloop<80, 1, 64, 2, true, false>(acc, sbase, bars, lane, wg, 10, wg * 5, wg != 0, rb, 1);
        epi_resid<false>(acc[0], res, g_x1, g_s.st1, smem, rowS, jS, lane);
        if (wg == 0) asm volatile("bar.arrive 5, 256;" ::: "memory");
        publish(fl + rbk, wg, tid);
      }
      {
        float acc[2][56];
        mainloop<112, 2, 64, 1, true, false>(acc, sbase, bars, lane, wg, 10, 10 + wg * 10, true, rb);
        mbar_wait(bars + BAR_AUX + wg * 8, 0);
        const float2 c0 = srow[rl], c1 = srow[rl + 8], c2 = srow[rl + 64], c3 = srow[rl + 72];
        const int cg0 = (c >> 1) * 27 + (c & 1) * 14;
        uint32_t* o0 = (uint32_t*)g_h + h_line(rbk * 128 + rl, cg0) * 32 + lane;
        int kg = cg0 % 12;
#pragma unroll
        for (int b = 0; b < 14; b++) {
          if (b < 13 || !(c & 1)) {
            const float2 cc = *(const float2*)(cs + b * 8 + q * 2);
            const uint32_t bb = sb1[b * 4 + q];
            const float bl = bf_lo(bb), bh = bf_hi(bb);
            o0[0] = pack_bf16(gelu_half(fmaf(c0.x, acc[0][4 * b], fmaf(c0.y, cc.x, bl))), gelu_half(fmaf(c0.x, acc[0][4 * b + 1], fmaf(c0.y, cc.y, bh))));
            o0[384] = pack_bf16(gelu_half(fmaf(c1.x, acc[0][4 * b + 2], fmaf(c1.y, cc.x, bl))), gelu_half(fmaf(c1.x, acc[0][4 * b + 3], fmaf(c1.y, cc.y, bh))));
            o0[18 * 3072] = pack_bf16(gelu_half(fmaf(c2.x, acc[1][4 * b], fmaf(c2.y, cc.x, bl))), gelu_half(fmaf(c2.x, acc[1][4 * b + 1], fmaf(c2.y, cc.y, bh))));
            o0[18 * 3072 + 384] = pack_bf16(gelu_half(fmaf(c3.x, acc[1][4 * b + 2], fmaf(c3.y, cc.x, bl))), gelu_half(fmaf(c3.x, acc[1][4 * b + 3], fmaf(c3.y, cc.y, bh))));
            o0 += (++kg == 12) ? (96 - 11) * 32 : 32;
            if (kg == 12) kg = 0;
          }
        }
        publish(fl + 16 + rbk, wg, tid);
      }
      {
        float acc[1][40];
#pragma unroll
        for (int b = 0; b < 10; b++) {
          const uint32_t bb = __ldg((const uint32_t*)(p.b2 + jS * 80) + b * 4 + q);
          acc[0][4 * b] = bf_lo(res[2 * b]) + bf_lo(bb); acc[0][4 * b + 1] = bf_hi(res[2 * b]) + bf_hi(bb);
          acc[0][4 * b + 2] = bf_lo(res[2 * b + 1]) + bf_lo(bb); acc[0][4 * b + 3] = bf_hi(res[2 * b + 1]) + bf_hi(bb);
        }
#pragma unroll 1
        for (int sg = 0; sg < 2; sg++)
          mainloop<80, 1, 96, 1, true, false, true>(acc, sbase, bars, lane, wg, sg ? 8 : 10, sg ? 20 + wg * 8 : wg * 10, !sg || (LAST ? wg == 0 : wg != 0), rb, 1);
        if (LAST) {
          const uint32_t st = (rb.s + wg) % SB;
          acquire_stage(bars, rb, st);
          epi_resid<true>(acc[0], res, nullptr, nullptr, smem + SM_B + st * STAGE, rowS, jS, lane);
          asm volatile("fence.proxy.async.shared::cta;" ::: "memory");
          named_bar(2 + wg, 128);
          if (t0) {
            asm volatile("cp.async.bulk.tensor.2d.global.shared::cta.bulk_group [%0, {%2, %3}], [%1];" ::"l"(&p.o_out), "r"(sbase + SM_B + st * STAGE), "r"(jS * 80),
                         "r"(rbk * 128 + (c & 1) * 64) : "memory");
            asm volatile("cp.async.bulk.commit_group;\ncp.async.bulk.wait_group 0;" ::: "memory");
          }
        } else {
          epi_resid<false>(acc[0], res, g_x2, g_s.st2, smem, rowS, jS, lane);
          if (wg == 0) asm volatile("bar.arrive 5, 256;" ::: "memory");
          publish(fl + 32 + rbk, wg, tid);
        }
      }
    }
    if (PH & PH_QKV) {
      float acc[2][60];
      mainloop<120, 2, 64, 1, !FIRST, true>(acc, sbase, bars, lane, wg, 10, (FIRST ? 0 : 30) + wg * 10, wg == 0, rb);
      mbar_wait(bars + BAR_AUX + 16 + wg * 8, 0);
      pdl_wait();
      const float QS = 0.22360679774997896f * 1.4426950408889634f;
      unsigned int* smax = sb1 + 16 + wg * 8;
      if ((tid & 127) < 6) smax[tid & 127] = 0u;
      named_bar(2 + wg, 128);
      int off[5];
#pragma unroll
      for (int m = 0; m < 5; m++) {
        const int cc = m * 8 + q * 2, hh = cc >= 20, d = cc - hh * 20;
        off[m] = hh * 6144 + (d >> 3) * 128 + (d & 7) * 2;
      }
#pragma unroll
      for (int pr = 0; pr < 3; pr++) {
        const int part = (c * 6 + pr * 2) >> 5;
        float nrm[2];
        const uint32_t sst = (rb.s + pr) % SB, soff = wg ? pr * STAGE : SM_B + sst * STAGE;
        if (wg == 0) acquire_stage(bars, rb, sst);
        uint8_t* stg = smem + soff + w4 * 768 + (lane >> 2) * 16;
#pragma unroll
        for (int mt = 0; mt < 2; mt++) {
          const float2 c0 = srow[mt * 64 + rl], c1 = srow[mt * 64 + rl + 8];
          const bool mu0 = is_mufu(mt * 8 + w4 * 2), mu1 = is_mufu(mt * 8 + w4 * 2 + 1), mu = (q & 1) ? mu1 : mu0;
          const float s0 = part == 0 ? QS : (part == 1 && !mu0 ? 0x1p-22f : 1.f), s1 = part == 0 ? QS : (part == 1 && !mu1 ? 0x1p-22f : 1.f);
          const float a0 = c0.x * s0, b0 = c0.y * s0, a1 = c1.x * s1, b1 = c1.y * s1;
          float nA0 = 0.f, nA1 = 0.f, nB0 = 0.f, nB1 = 0.f;
#pragma unroll
          for (int m = 0; m < 5; m++) {
            const int b = pr * 5 + m;
            const float2 cc = *(const float2*)(cs + b * 8 + q * 2);
            uint8_t* ptr = stg + off[m] + mt * 3072;
            const float v0 = fmaf(a0, acc[mt][4 * b], b0 * cc.x), v1 = fmaf(a0, acc[mt][4 * b + 1], b0 * cc.y);
            const float v2 = fmaf(a1, acc[mt][4 * b + 2], b1 * cc.x), v3 = fmaf(a1, acc[mt][4 * b + 3], b1 * cc.y);
            *(uint32_t*)ptr = pack_bf16(v0, v1);
            *(uint32_t*)(ptr + 384) = pack_bf16(v2, v3);
            const float n0 = fmaf(v0, v0, v1 * v1), n1 = fmaf(v2, v2, v3 * v3);
            if (m < 2) { nA0 += n0; nA1 += n1; } else if (m > 2) { nB0 += n0; nB1 += n1; }
            else if (q < 2) { nA0 += n0; nA1 += n1; } else { nB0 += n0; nB1 += n1; }
          }
          const uint2 ex = part == 0 ? make_uint2(0x3F803F80u, 0x00003F80u)
                                     : (part == 1 ? (mu ? make_uint2(0u, 0u) : make_uint2(0x377C3C00u, 0x00003020u)) : make_uint2(0x00003F80u, 0u));
          *(uint2*)(stg + mt * 3072 + (q >> 1) * 6144 + (q & 1) * 384 + 264) = ex;
          float x = (q & 1) ? nA1 : nA0, y = (q & 1) ? nB1 : nB0;
          x += __shfl_xor_sync(0xffffffffu, (q & 1) ? nA0 : nA1, 1);
          y += __shfl_xor_sync(0xffffffffu, (q & 1) ? nB0 : nB1, 1);
          float n = (q & 2) ? y : x;
          n += __shfl_xor_sync(0xffffffffu, (q & 2) ? x : y, 2);
          nrm[mt] = (part == 1 && !mu) ? n * 0x1p44f : n;
        }
        asm volatile("fence.proxy.async.shared::cta;" ::: "memory");
        named_bar(2 + wg, 128);
        if ((tid & 127) < 2) bulk_s2g((uint8_t*)g_qkv + (size_t)(c * 6 + pr * 2 + lane) * HEAD_BYTES + rbk * 6144, sbase + soff + lane * 6144, 6144);
        if (part < 2) atomicMax(smax + pr * 2 + (q >> 1), max(__float_as_uint(nrm[0]) & 0x7FFFFFFFu, __float_as_uint(nrm[1]) & 0x7FFFFFFFu));
      }
      named_bar(2 + wg, 128);
      if ((tid & 127) < 6 && c * 6 + (tid & 127) < 64) atomicMax(fl + NORM_OFF + c * 6 + (tid & 127), smax[tid & 127]);
      if ((tid & 127) < 2) {
        asm volatile("cp.async.bulk.wait_group 0;" ::: "memory");
      }
    }
  }
}

__device__ __forceinline__ uint32_t exp2_poly_pair(float a0, float a1) {
  const uint32_t v = __byte_perm(__float_as_uint(a0), __float_as_uint(a1), 0x7430);
  const uint32_t e = __byte_perm(__float_as_uint(a0), __float_as_uint(a1), 0x6521);
  uint32_t u;
  asm("fma.rn.f16x2 %0, %1, %2, %3;" : "=r"(u) : "r"(v), "r"(0x1d611d61u), "r"(0xa012a012u));
  asm("fma.rn.f16x2 %0, %1, %2, %3;" : "=r"(u) : "r"(u), "r"(v), "r"(0x21622162u));
  uint32_t r;
  asm("{\n.reg .b32 t;\nshl.b32 t, %1, 7;\nadd.u32 %0, t, %2;\n}" : "=r"(r) : "r"(e), "r"(u));
  return r;
}
constexpr int KPITCH = 6144 + 128;
constexpr int ATT_V = 16 * KPITCH, ATT_JOB = ATT_V + HEAD_BYTES, ATT_BAR = ATT_JOB + 2 * 15360, ATT_SMEM = ATT_BAR + 128;

__device__ __forceinline__ void att_store(const float (&O)[12], int row0, int h, int lane) {
  const float l0 = __shfl_sync(0xffffffffu, O[8], (lane & ~3) | 2), l1 = __shfl_sync(0xffffffffu, O[10], (lane & ~3) | 2);
  const float r0 = __fdividef(1.f, l0), r1 = __fdividef(1.f, l1);
#pragma unroll
  for (int c = 0; c < 3; c++)
    if (c < 2 || (lane & 3) < 2) {
      const int col = h * 20 + c * 8 + (lane & 3) * 2;
      uint32_t* o0 = (uint32_t*)g_o + o_line(row0, col >> 3) * 32 + (row0 & 7) * 4 + ((col & 7) >> 1);
      o0[0] = pack_bf16(O[4 * c] * r0, O[4 * c + 1] * r0);
      o0[256] = pack_bf16(O[4 * c + 2] * r1, O[4 * c + 3] * r1);
    }
}

struct alignas(64) AttParams {
  CUtensorMap b_w2;
  const unsigned int* norms;
  unsigned int *reset_a, *reset_b, *reset_c;
  const uint32_t* zeros;
  int jobs;
};
__global__ void __launch_bounds__(512, 1) att_kernel(const __grid_constant__ AttParams p) {
  const unsigned int* norms = p.norms;
  extern __shared__ __align__(1024) uint8_t smem[];
  const uint32_t sK = smem_u32(smem), sV = sK + ATT_V, bars = sK + ATT_BAR;
  const int h = blockIdx.x >> 2, qt = blockIdx.x & 3;
  const int tid = threadIdx.x, lane = tid & 31, wg = __shfl_sync(0xffffffffu, tid >> 7, 0), warp = (tid >> 5) & 3;
  if (tid == 0) {
    for (int c = 0; c < 9; c++) mbar_init(bars + c * 8, 1);
    asm volatile("fence.mbarrier_init.release.cluster;" ::: "memory");
  }
  *(uint32_t*)(smem + (tid >> 5) * KPITCH + 6144 + lane * 4) = 0u;
  asm volatile("fence.proxy.async;" ::: "memory");
  const uint32_t z0 = __ldg(p.zeros + (tid & 1)), z1 = __ldg(p.zeros + 2 + (tid & 1));
  __syncthreads();
  pdl_wait();
  pdl_launch();
  const uint8_t* gq = (const uint8_t*)g_qkv + (size_t)h * HEAD_BYTES;
  const uint64_t dK = mk_desc(sK, 128, 384, 0);
  const uint64_t dV = mk_desc(sV, 384, 128, 0);
  uint32_t q[6];
  auto load_q = [&](int row0) {
    const uint32_t* qa = (const uint32_t*)(gq + (row0 >> 3) * 384 + (row0 & 7) * 16) + (lane & 3);
    q[0] = __ldcg(qa); q[1] = __ldcg(qa + 96); q[2] = __ldcg(qa + 32); q[3] = __ldcg(qa + 128); q[4] = __ldcg(qa + 64); q[5] = __ldcg(qa + 160);
  };
  const int rowA = qt * 512 + wg * 64 + warp * 16 + (lane >> 2);
  load_q(rowA);
  auto load_kv = [&](int c) {
    mbar_expect_tx(bars + c * 8, 24576);
    bulk_g2s(sK + c * 2 * KPITCH, gq + 32 * HEAD_BYTES + c * 12288, 6144, bars + c * 8);
    bulk_g2s(sK + (c * 2 + 1) * KPITCH, gq + 32 * HEAD_BYTES + c * 12288 + 6144, 6144, bars + c * 8);
    bulk_g2s(sV + c * 12288, gq + 64 * HEAD_BYTES + c * 12288, 12288, bars + c * 8);
  };
  if (tid == 480) { load_kv(0); load_kv(1); }
  __syncwarp();
  auto load_rest = [&]() {
        if (tid == 480) {
#pragma unroll 1
          for (int c = 2; c < 8; c++) load_kv(c);
          if (p.jobs) {
            mbar_expect_tx(bars + 64, blockIdx.x < 16 ? 30720 : 15360);
#pragma unroll 1
            for (int job = blockIdx.x; job < 144; job += 128)
#pragma unroll 1
              for (int b = 0; b < 5; b++) tma_3d(sK + ATT_JOB + (job >> 7) * 15360 + b * 3072, &p.b_w2, b * 16, job / 18, (job % 18) * 96, bars + 64);
          }
        }
        __syncwarp();
  };
  const bool unsafe = !(__uint_as_float(__ldcg(norms + h)) * __uint_as_float(__ldcg(norms + 32 + h)) <= 3500.f);
  if (blockIdx.x == 0 && tid < NORM_OFF) { p.reset_a[tid] = 0u; if (tid < FLAG_SET - NORM_OFF) p.reset_b[tid] = 0u; if (p.reset_c) p.reset_c[tid] = 0u; }
  auto fast_tile = [&](auto first, int row0) -> bool {
      constexpr int tt = first.value ? 0 : 1;
      float S[64], O[12];
      uint32_t P[32];
#pragma unroll
      for (int k = 0; k < 64; k++) S[k] = 0.f;
#pragma unroll
      for (int k = 0; k < 12; k++) O[k] = 0.f;
      auto blocks = [&](int g0, int g1) {
        uint64_t gk = dK + g0 * (KPITCH / 16), gv = dV + g0 * 384;
#pragma unroll 1
        for (int g = g0; g < g1; g++) {
        if (tt == 0 && (g & 1) == 0) mbar_wait_warp(bars + (g >> 1) * 8, 0);
        wg_fence();
        wgmma_rs_n128<0>(S, q[0], q[1], q[2], q[3], gk, 0);
        wgmma_rs_n128<0>(S, q[4], q[5], z0, z1, gk + 16, 1);
        wg_commit();
        wg_wait<0>();
        fence_regs(S);
#pragma unroll
        for (int hf = 0; hf < 4; hf++) {
          constexpr int NB = 16 / 4;
          uint32_t (&Ph)[2 * NB] = *(uint32_t(*)[2 * NB])(P + hf * 2 * NB);
#pragma unroll
          for (int b = hf * NB; b < hf * NB + NB; b++) {
            if (is_mufu(b)) { P[2 * b] = pack_bf16(ex2(S[4 * b]), ex2(S[4 * b + 1])); P[2 * b + 1] = pack_bf16(ex2(S[4 * b + 2]), ex2(S[4 * b + 3])); }
            else { P[2 * b] = exp2_poly_pair(S[4 * b], S[4 * b + 1]); P[2 * b + 1] = exp2_poly_pair(S[4 * b + 2], S[4 * b + 3]); }
          }
          fence_regs(Ph);
          wg_fence();
#pragma unroll
          for (int s = hf * NB / 2; s < (hf + 1) * NB / 2; s++) wgmma_rs_n24<1>(O, P[4 * s], P[4 * s + 1], P[4 * s + 2], P[4 * s + 3], gv + s * 48, 1);
          wg_commit();
        }
        wg_wait<0>();
        gk += KPITCH / 16; gv += 384;
        }
      };
      if (tt == 0) {
        blocks(0, 2);
        load_rest();
        blocks(2, 16);
      } else blocks(0, 16);
      fence_regs(O);
      att_store(O, row0, h, lane);
      bool bad = false;
      float m = 0.f;
#pragma unroll
      for (int k = 0; k < 12; k++) { m = fmaxf(m, fabsf(O[k])); bad |= (O[k] != O[k]); }
      bad |= !(m <= 3e38f);
      if ((lane & 3) == 2) bad |= !(O[8] >= 0x1p-20f) || !(O[10] >= 0x1p-20f);
      uint32_t r;
      asm volatile("{\n.reg .pred p, r;\nsetp.ne.u32 p, %1, 0;\nbarrier.red.or.pred.aligned r, %2, 128, p;\nselp.u32 %0, 1, 0, r;\n}\n" : "=r"(r) : "r"((uint32_t)bad), "r"(1 + wg) : "memory");
      return r != 0;
  };
  auto safe_tile = [&](int row0) {
      float S[64], O[12];
      uint32_t P[32];
#pragma unroll
      for (int k = 0; k < 64; k++) S[k] = 0.f;
      if ((lane & 3) >= 2) { q[4] = 0u; q[5] = 0u; }
      float m0 = -INFINITY, m1 = -INFINITY;
#pragma unroll
      for (int k = 0; k < 12; k++) O[k] = 0.f;
      uint64_t gk = dK, gv = dV;
#pragma unroll 1
      for (int g = 0; g < 16; g++) {
        wg_fence();
        wgmma_rs_n128<0>(S, q[0], q[1], q[2], q[3], gk, 0);
        wgmma_rs_n128<0>(S, q[4], q[5], z0, z1, gk + 16, 1);
        wg_commit();
        wg_wait<0>();
        fence_regs(S);
        float x0 = m0, x1 = m1;
#pragma unroll
        for (int b = 0; b < 16; b++) {
          if (!is_mufu(b)) { S[4 * b] *= 0x1p22f; S[4 * b + 1] *= 0x1p22f; S[4 * b + 2] *= 0x1p22f; S[4 * b + 3] *= 0x1p22f; }
          x0 = fmaxf(x0, fmaxf(S[4 * b], S[4 * b + 1]));
          x1 = fmaxf(x1, fmaxf(S[4 * b + 2], S[4 * b + 3]));
        }
        x0 = fmaxf(x0, __shfl_xor_sync(0xffffffffu, x0, 1)); x1 = fmaxf(x1, __shfl_xor_sync(0xffffffffu, x1, 1));
        x0 = fmaxf(x0, __shfl_xor_sync(0xffffffffu, x0, 2)); x1 = fmaxf(x1, __shfl_xor_sync(0xffffffffu, x1, 2));
        const float al0 = ex2(m0 - x0), al1 = ex2(m1 - x1);
        m0 = x0; m1 = x1;
#pragma unroll
        for (int c = 0; c < 3; c++) { O[4 * c] *= al0; O[4 * c + 1] *= al0; O[4 * c + 2] *= al1; O[4 * c + 3] *= al1; }
#pragma unroll
        for (int b = 0; b < 16; b++) {
          P[2 * b] = pack_bf16(ex2(S[4 * b] - m0), ex2(S[4 * b + 1] - m0));
          P[2 * b + 1] = pack_bf16(ex2(S[4 * b + 2] - m1), ex2(S[4 * b + 3] - m1));
        }
        fence_regs(P);
        fence_regs(O);
        wg_fence();
#pragma unroll
        for (int s = 0; s < 8; s++) wgmma_rs_n24<1>(O, P[4 * s], P[4 * s + 1], P[4 * s + 2], P[4 * s + 3], gv + s * 48, 1);
        wg_commit();
        wg_wait<0>();
        fence_regs(O);
        gk += KPITCH / 16; gv += 384;
      }
      att_store(O, row0, h, lane);
      named_bar(1 + wg, 128);
  };
  bool redo = true;
  if (!__any_sync(0xffffffffu, unsafe)) redo = fast_tile(IC<1>{}, rowA);
  else {
    load_rest();
#pragma unroll 1
    for (int c = 0; c < 8; c++) mbar_wait(bars + c * 8, 0);
  }
  if (__any_sync(0xffffffffu, redo)) safe_tile(rowA);
  load_q(rowA + 256);
  if (tid == 480 && p.jobs) {
    mbar_wait(bars + 64, 0);
#pragma unroll 1
    for (int job = blockIdx.x; job < 144; job += 128) bulk_s2g(g_wt + WT_W2 + job * 15360, sK + ATT_JOB + (job >> 7) * 15360, 15360);
  }
  __syncwarp();
  redo = true;
  if (!__any_sync(0xffffffffu, unsafe)) redo = fast_tile(IC<0>{}, rowA + 256);
  if (__any_sync(0xffffffffu, redo)) safe_tile(rowA + 256);
  if (tid == 480) asm volatile("cp.async.bulk.wait_group 0;" ::: "memory");
}

typedef CUresult (*EncodeFn)(CUtensorMap*, CUtensorMapDataType, cuuint32_t, void*, const cuuint64_t*, const cuuint64_t*, const cuuint32_t*,
                             const cuuint32_t*, CUtensorMapInterleave, CUtensorMapSwizzle, CUtensorMapL2promotion, CUtensorMapFloatOOBfill);

static void make_a(EncodeFn enc, CUtensorMap* m, const void* ptr, int K) {
  cuuint64_t dims[2] = {(cuuint64_t)K, (cuuint64_t)SEQ}, strides[1] = {(cuuint64_t)K * 2};
  cuuint32_t box[2] = {64, 128}, es[2] = {1, 1};
  enc(m, CU_TENSOR_MAP_DATA_TYPE_BFLOAT16, 2, (void*)ptr, dims, strides, box, es, CU_TENSOR_MAP_INTERLEAVE_NONE, CU_TENSOR_MAP_SWIZZLE_128B,
      CU_TENSOR_MAP_L2_PROMOTION_NONE, CU_TENSOR_MAP_FLOAT_OOB_FILL_NONE);
}
static void make_out(EncodeFn enc, CUtensorMap* m, void* ptr) {
  cuuint64_t dims[2] = {(cuuint64_t)DM, (cuuint64_t)SEQ}, strides[1] = {(cuuint64_t)DM * 2};
  cuuint32_t box[2] = {80, 64}, es[2] = {1, 1};
  enc(m, CU_TENSOR_MAP_DATA_TYPE_BFLOAT16, 2, ptr, dims, strides, box, es, CU_TENSOR_MAP_INTERLEAVE_NONE, CU_TENSOR_MAP_SWIZZLE_NONE,
      CU_TENSOR_MAP_L2_PROMOTION_NONE, CU_TENSOR_MAP_FLOAT_OOB_FILL_NONE);
}
static void make_b(EncodeFn enc, CUtensorMap* m, const void* ptr, int K, int N, int BN, int bk, int bw) {
  cuuint64_t dims[3] = {(cuuint64_t)BN, (cuuint64_t)(N / BN), (cuuint64_t)K}, strides[2] = {(cuuint64_t)BN * 2, (cuuint64_t)N * 2};
  cuuint32_t box[3] = {(cuuint32_t)bw, 1, (cuuint32_t)bk}, es[3] = {1, 1, 1};
  enc(m, CU_TENSOR_MAP_DATA_TYPE_BFLOAT16, 3, (void*)ptr, dims, strides, box, es, CU_TENSOR_MAP_INTERLEAVE_NONE, bw == 64 ? CU_TENSOR_MAP_SWIZZLE_128B : CU_TENSOR_MAP_SWIZZLE_32B,
      CU_TENSOR_MAP_L2_PROMOTION_NONE, CU_TENSOR_MAP_FLOAT_OOB_FILL_NONE);
}
template <typename... KArgs, typename... Args>
static void launch(void (*kern)(KArgs...), int grid, int threads, int smem, bool pdl, Args... args) {
  cudaFuncSetAttribute(kern, cudaFuncAttributeMaxDynamicSharedMemorySize, smem);
  cudaLaunchConfig_t cfg = {};
  cfg.gridDim = dim3(grid); cfg.blockDim = dim3(threads); cfg.dynamicSmemBytes = smem; cfg.stream = cudaStreamPerThread;
  cudaLaunchAttribute at[1];
  at[0].id = cudaLaunchAttributeProgrammaticStreamSerialization; at[0].val.programmaticStreamSerializationAllowed = 1;
  cfg.attrs = at; cfg.numAttrs = pdl ? 1 : 0;
  cudaLaunchKernelEx(&cfg, kern, KArgs(args)...);
}

static void make_pref(signed char* pref, int ntpc) {
  auto kern = chain_kernel<PH_WO | PH_W1 | PH_W2, false, true>;
  cudaFuncSetAttribute(kern, cudaFuncAttributeMaxDynamicSharedMemorySize, CHAIN_SMEM);
  cudaFuncSetAttribute(kern, cudaFuncAttributeNonPortableClusterSizeAllowed, 1);
  int n[10] = {0};
  for (int t = 2; t <= 8; t++) {
    cudaLaunchConfig_t cfg = {};
    cfg.gridDim = dim3(2 * t * 16); cfg.blockDim = dim3(CHAIN_THREADS); cfg.dynamicSmemBytes = CHAIN_SMEM;
    cudaLaunchAttribute at[1];
    at[0].id = cudaLaunchAttributeClusterDimension; at[0].val.clusterDim.x = 2 * t; at[0].val.clusterDim.y = 1; at[0].val.clusterDim.z = 1;
    cfg.attrs = at; cfg.numAttrs = 1;
    if (cudaOccupancyMaxActiveClusters(&n[t], kern, &cfg) != cudaSuccess) { n[t] = -1; cudaGetLastError(); }
  }
  int best[10] = {0}, cnt[10], found = 0;
  for (int code = 0; code < 1000000 && !found; code++) {
    int c = code, tot = 0, g = 0;
    for (int m = 0; m < 10; m++) cnt[m] = 0;
    for (int m = 4; m <= 9; m++) { cnt[m] = c % 10; c /= 10; tot += cnt[m] * m; g += cnt[m]; }
    if (g > 9 || tot > ntpc) continue;
    bool ok = true;
    for (int t = 3; t <= 8 && ok; t++) { int s = 0; for (int m = 4; m <= 9; m++) s += cnt[m] * (m / t); ok = (s == n[t]); }
    if (ok) { found = 1; for (int m = 0; m < 10; m++) best[m] = cnt[m]; }
  }
  int grp[80], size[10], ng = 0, id = 0;
  for (int t = 0; t < 80; t++) { grp[t] = -1; pref[2 * t] = pref[2 * t + 1] = -1; }
  if (found) {
    for (int m = 4; m <= 9; m++) for (int k = 0; k < best[m]; k++) size[ng++] = m;
    for (int r = 0; r < 9; r++) for (int g = 0; g < ng; g++) if (size[g] > r && id < ntpc) grp[id++] = g;
  }
  int nb = 0;
  bool used[80] = {false};
  auto put = [&](int t, int blk, int w) {
    const int tile = blk * 16 + w * 2;
    pref[2 * t] = (signed char)tile; pref[2 * t + 1] = (signed char)(tile + 1); used[t] = true;
  };
  for (int g = 0; g < ng && nb < 8; g++)
    if (size[g] >= 8) {
      int w = 0;
      for (int t = 0; t < ntpc && w < 8; t++) if (grp[t] == g) put(t, nb, w++);
      nb++;
    }
  int pos = nb * 8;
  for (int pass = 0; pass < 2; pass++)
    for (int g = 0; g <= ng; g++)
      for (int t = 0; t < ntpc && pos < 64; t++)
        if (!used[t] && (g < ng ? (grp[t] == g && (size[g] < 8) == (pass == 0)) : (pass == 1 && grp[t] < 0))) { put(t, pos >> 3, pos & 7); pos++; }
}

extern "C" void kernel_launch(void* const* d_in, const int* in_sizes, int n_in, void* d_out, int out_size) {
  const bf16* x = (const bf16*)d_in[0];
  const bf16* wqkv = (const bf16*)d_in[1];
  const bf16* wo = (const bf16*)d_in[2];
  const bf16* w1 = (const bf16*)d_in[4];
  const bf16* b1 = (const bf16*)d_in[5];
  const bf16* w2 = (const bf16*)d_in[6];
  const bf16* b2 = (const bf16*)d_in[7];
  void* fn = nullptr;
  cudaDriverEntryPointQueryResult qr;
  cudaGetDriverEntryPoint("cuTensorMapEncodeTiled", &fn, cudaEnableDefault, &qr);
  EncodeFn enc = (EncodeFn)fn;
  void *px0, *px2, *pf, *pz;
  cudaGetSymbolAddress(&px0, g_x0);
  cudaGetSymbolAddress(&px2, g_x2); cudaGetSymbolAddress(&pf, g_s);
  unsigned int* flags = ((Small*)pf)->flags;
  pz = ((Small*)pf)->zeros;

  int nsm = 132;
  cudaDeviceGetAttribute(&nsm, cudaDevAttrMultiProcessorCount, 0);
  const int ngrid = nsm >= 128 ? (nsm > 160 ? 160 : (nsm & ~1)) : 128;
  ChainParams p;
  make_pref(p.pref, ngrid / 2);
  make_a(enc, &p.a_x, x, DM);
  make_out(enc, &p.o_out, d_out);
  AttParams ap;
  make_b(enc, &p.b_wo, wo, DM, DM, 80, 64, 16); make_b(enc, &p.b_w1, w1, DM, FF, 216, 64, 16); make_b(enc, &ap.b_w2, w2, FF, DM, 80, 96, 16);
  ap.zeros = (const uint32_t*)pz;
  make_b(enc, &p.b_wqkv, wqkv, DM, 1920, 120, 64, 64);
  p.xres = (const bf16*)px0; p.xin = x; p.b1 = b1; p.b2 = b2; p.flags = flags;

  launch(chain_kernel<PH_QKV, true, false>, ngrid, CHAIN_THREADS, CHAIN_SMEM, false, p);
  ap.norms = flags + NORM_OFF; ap.reset_a = flags; ap.reset_b = flags + FLAG_SET + NORM_OFF; ap.reset_c = flags + 2 * FLAG_SET; ap.jobs = 1;
  launch(att_kernel, 128, 512, ATT_SMEM, true, ap);
  p.flags = flags + FLAG_SET;
  launch(chain_kernel<PH_WO | PH_W1 | PH_W2 | PH_QKV, false, false>, ngrid, CHAIN_THREADS, CHAIN_SMEM, true, p);
  ap.norms = flags + FLAG_SET + NORM_OFF; ap.reset_a = flags + FLAG_SET; ap.reset_b = flags + NORM_OFF; ap.reset_c = nullptr; ap.jobs = 0;
  launch(att_kernel, 128, 512, ATT_SMEM, true, ap);
  p.xres = (const bf16*)px2; p.flags = flags + 2 * FLAG_SET;
  launch(chain_kernel<PH_WO | PH_W1 | PH_W2, false, true>, ngrid, CHAIN_THREADS, CHAIN_SMEM, true, p);
}
```

```cpp
#include <cuda_runtime.h>
#include <cuda_bf16.h>
#include <cuda.h>
#include <stdint.h>

typedef __nv_bfloat16 bf16;

constexpr int SEQ = 2048, DM = 640, FF = 1728;
constexpr float LN_EPS = 1e-5f;
constexpr int HEAD_BYTES = 98304;
constexpr uint32_t MUFU_MASK = 0x1259u;
__host__ __device__ constexpr bool is_mufu(int g) { return (MUFU_MASK >> (g & 15)) & 1u; }

__device__ __align__(1024) bf16 g_qkv[96 * (HEAD_BYTES / 2)];
constexpr int WT_WO = 0, WT_W1 = WT_WO + 80 * 10240, WT_W2 = WT_W1 + 160 * 14336, WT_QKV = WT_W2 + 144 * 15360, WT_END = WT_QKV + 160 * 16384;
__device__ __align__(1024) uint8_t g_wt[WT_END];
__device__ __forceinline__ int x_line(int row, int cg) { return (((row >> 7) * 10 + (cg >> 3)) * 16 + ((row >> 3) & 15)) * 8 + (cg & 7); }
__device__ __forceinline__ int o_line(int row, int cg) { return (((row >> 6) * 10 + (cg >> 3)) * 8 + ((row >> 3) & 7)) * 8 + (cg & 7); }
__device__ __forceinline__ int h_line(int row, int cg) { return (((row >> 6) * 18 + cg / 12) * 8 + ((row >> 3) & 7)) * 12 + cg % 12; }
__device__ __align__(1024) bf16 g_x0[SEQ * DM];
__device__ __align__(1024) bf16 g_o[SEQ * DM];
__device__ __align__(1024) bf16 g_x1[SEQ * DM];
__device__ __align__(1024) bf16 g_x2[SEQ * DM];
__device__ __align__(1024) bf16 g_h[SEQ * FF];
constexpr int FLAG_SET = 320, NORM_OFF = 256;
struct Small {
  float2 st0[2 * SEQ];
  float2 st1[8 * SEQ];
  float2 st2[8 * SEQ];
  float csp_w1[10 * 1792];
  float cs_qkv[1920];
  unsigned int flags[3 * FLAG_SET];
  uint32_t zeros[4];
};
__device__ __align__(1024) Small g_s;

__device__ __forceinline__ uint32_t smem_u32(const void* p) { return (uint32_t)__cvta_generic_to_shared(p); }
__device__ __forceinline__ void mbar_init(uint32_t bar, int cnt) { asm volatile("mbarrier.init.shared::cta.b64 [%0], %1;" ::"r"(bar), "r"(cnt) : "memory"); }
__device__ __forceinline__ void mbar_expect_tx(uint32_t bar, uint32_t bytes) { asm volatile("mbarrier.arrive.expect_tx.shared::cta.b64 _, [%0], %1;" ::"r"(bar), "r"(bytes) : "memory"); }
__device__ __forceinline__ void mbar_arrive(uint32_t bar) { asm volatile("mbarrier.arrive.shared::cta.b64 _, [%0];" ::"r"(bar) : "memory"); }
__device__ __forceinline__ void mbar_arrive_if(uint32_t bar, bool c) {
  asm volatile("{\n.reg .pred p;\nsetp.ne.u32 p, %1, 0;\n@p mbarrier.arrive.shared::cta.b64 _, [%0];\n}\n" ::"r"(bar), "r"((uint32_t)c) : "memory");
}
__device__ __forceinline__ bool mbar_try(uint32_t bar, uint32_t parity) {
  uint32_t ok;
  asm volatile("{\n.reg .pred p;\nmbarrier.try_wait.parity.shared::cta.b64 p, [%1], %2;\nselp.u32 %0, 1, 0, p;\n}\n" : "=r"(ok) : "r"(bar), "r"(parity) : "memory");
  return ok != 0;
}
__device__ __forceinline__ bool mbar_test(uint32_t bar, uint32_t parity) {
  uint32_t ok;
  asm volatile("{\n.reg .pred p;\nmbarrier.test_wait.parity.shared::cta.b64 p, [%1], %2;\nselp.u32 %0, 1, 0, p;\n}\n" : "=r"(ok) : "r"(bar), "r"(parity) : "memory");
  return ok != 0;
}
__device__ __forceinline__ void mbar_wait(uint32_t bar, uint32_t parity) {
  if (mbar_try(bar, parity)) return;
#pragma unroll 1
  for (int it = 0; it < (1 << 22); it++)
    if (mbar_try(bar, parity)) return;
  __trap();
}
__device__ __forceinline__ void mbar_wait_warp(uint32_t bar, uint32_t parity) {
#pragma unroll 1
  for (int it = 0; !__all_sync(0xffffffffu, mbar_try(bar, parity)); it++)
    if (it > (1 << 22)) __trap();
}
__device__ __forceinline__ void flag_wait(const unsigned int* f, unsigned int target) {
  unsigned int v;
#pragma unroll 1
  for (int it = 0; it < (1 << 22); it++) {
    asm volatile("ld.acquire.gpu.global.u32 %0, [%1];" : "=r"(v) : "l"(f) : "memory");
    if (v >= target) return;
  }
  __trap();
}
__device__ __forceinline__ void flag_signal(unsigned int* f) { asm volatile("red.release.gpu.global.add.u32 [%0], 1;" ::"l"(f) : "memory"); }
__device__ __forceinline__ void fence_async_global() { asm volatile("fence.proxy.async.global;" ::: "memory"); }
__device__ __forceinline__ void pdl_wait() { asm volatile("griddepcontrol.wait;" ::: "memory"); }
__device__ __forceinline__ void pdl_launch() { asm volatile("griddepcontrol.launch_dependents;" ::: "memory"); }
__device__ __forceinline__ void named_bar(int id, int n) { asm volatile("bar.sync %0, %1;" ::"r"(id), "r"(n) : "memory"); }
__device__ __forceinline__ void bulk_g2s(uint32_t dst, const void* src, uint32_t bytes, uint32_t bar) {
  asm volatile("cp.async.bulk.shared::cluster.global.mbarrier::complete_tx::bytes [%0], [%1], %2, [%3];" ::"r"(dst), "l"(src), "r"(bytes), "r"(bar) : "memory");
}
__device__ __forceinline__ void tma_2d(uint32_t dst, const CUtensorMap* m, int c0, int c1, uint32_t bar) {
  asm volatile("cp.async.bulk.tensor.2d.shared::cluster.global.mbarrier::complete_tx::bytes [%0], [%1, {%3, %4}], [%2];" ::"r"(dst), "l"(m), "r"(bar), "r"(c0), "r"(c1) : "memory");
}
__device__ __forceinline__ void tma_3d(uint32_t dst, const CUtensorMap* m, int c0, int c1, int c2, uint32_t bar) {
  asm volatile("cp.async.bulk.tensor.3d.shared::cluster.global.mbarrier::complete_tx::bytes [%0], [%1, {%3, %4, %5}], [%2];" ::"r"(dst), "l"(m), "r"(bar), "r"(c0), "r"(c1), "r"(c2) : "memory");
}
__device__ __forceinline__ void prefetch_map(const CUtensorMap* m) { asm volatile("prefetch.tensormap [%0];" ::"l"(m) : "memory"); }
__device__ __forceinline__ void wg_fence() { asm volatile("wgmma.fence.sync.aligned;" ::: "memory"); }
__device__ __forceinline__ void wg_commit() { asm volatile("wgmma.commit_group.sync.aligned;" ::: "memory"); }
template <int N> __device__ __forceinline__ void wg_wait() { asm volatile("wgmma.wait_group.sync.aligned %0;" ::"n"(N) : "memory"); }
template <int N> __device__ __forceinline__ void fence_regs(float (&d)[N]) {
#pragma unroll
  for (int i = 0; i < N; i++) asm volatile("" : "+f"(d[i])::"memory");
}
template <int N> __device__ __forceinline__ void fence_regs(uint32_t (&d)[N]) {
#pragma unroll
  for (int i = 0; i < N; i++) asm volatile("" : "+r"(d[i])::"memory");
}
__device__ __forceinline__ uint64_t mk_desc(uint32_t addr, uint32_t lbo, uint32_t sbo, uint64_t swz) {
  return (uint64_t)((addr & 0x3FFFF) >> 4) | ((uint64_t)(lbo >> 4) << 16) | ((uint64_t)(sbo >> 4) << 32) | (swz << 62);
}
__device__ __forceinline__ uint32_t pack_bf16(float lo, float hi) {
  uint32_t r;
  asm("cvt.rn.bf16x2.f32 %0, %1, %2;" : "=r"(r) : "f"(hi), "f"(lo));
  return r;
}
__device__ __forceinline__ float bf_lo(uint32_t v) { return __uint_as_float(v << 16); }
__device__ __forceinline__ float bf_hi(uint32_t v) { return __uint_as_float(v & 0xFFFF0000u); }
__device__ __forceinline__ float ex2(float x) { float r; asm("ex2.approx.ftz.f32 %0, %1;" : "=f"(r) : "f"(x)); return r; }

template<int TB> __device__ __forceinline__ void wgmma_rs_n24(float (&d)[12], uint32_t a0, uint32_t a1, uint32_t a2, uint32_t a3, uint64_t db, int sd) {
  asm volatile("{\n.reg .pred p;\nsetp.ne.b32 p, %17, 0;\n"
    "wgmma.mma_async.sync.aligned.m64n24k16.f32.bf16.bf16 "
    "{%0,%1,%2,%3,%4,%5,%6,%7,%8,%9,%10,%11}, "
    "{%12,%13,%14,%15}, %16, p, 1, 1, %18;\n}\n"
    : "+f"(d[0]),"+f"(d[1]),"+f"(d[2]),"+f"(d[3]),"+f"(d[4]),"+f"(d[5]),"+f"(d[6]),"+f"(d[7]),"+f"(d[8]),"+f"(d[9]),"+f"(d[10]),"+f"(d[11])
    : "r"(a0), "r"(a1), "r"(a2), "r"(a3), "l"(db), "r"(sd), "n"(TB));
}
template<int TB> __device__ __forceinline__ void wgmma_rs_n120(float (&d)[60], uint32_t a0, uint32_t a1, uint32_t a2, uint32_t a3, uint64_t db, int sd) {
  asm volatile("{\n.reg .pred p;\nsetp.ne.b32 p, %65, 0;\n"
    "wgmma.mma_async.sync.aligned.m64n120k16.f32.bf16.bf16 "
    "{%0,%1,%2,%3,%4,%5,%6,%7,%8,%9,%10,%11,%12,%13,%14,%15,%16,%17,%18,%19,%20,%21,%22,%23,%24,%25,%26,%27,%28,%29,%30,%31,%32,%33,%34,%35,%36,%37,%38,%39,%40,%41,%42,%43,%44,%45,%46,%47,%48,%49,%50,%51,%52,%53,%54,%55,%56,%57,%58,%59}, "
    "{%60,%61,%62,%63}, %64, p, 1, 1, %66;\n}\n"
    : "+f"(d[0]),"+f"(d[1]),"+f"(d[2]),"+f"(d[3]),"+f"(d[4]),"+f"(d[5]),"+f"(d[6]),"+f"(d[7]),"+f"(d[8]),"+f"(d[9]),"+f"(d[10]),"+f"(d[11]),"+f"(d[12]),"+f"(d[13]),"+f"(d[14]),"+f"(d[15]),"+f"(d[16]),"+f"(d[17]),"+f"(d[18]),"+f"(d[19]),"+f"(d[20]),"+f"(d[21]),"+f"(d[22]),"+f"(d[23]),"+f"(d[24]),"+f"(d[25]),"+f"(d[26]),"+f"(d[27]),"+f"(d[28]),"+f"(d[29]),"+f"(d[30]),"+f"(d[31]),"+f"(d[32]),"+f"(d[33]),"+f"(d[34]),"+f"(d[35]),"+f"(d[36]),"+f"(d[37]),"+f"(d[38]),"+f"(d[39]),"+f"(d[40]),"+f"(d[41]),"+f"(d[42]),"+f"(d[43]),"+f"(d[44]),"+f"(d[45]),"+f"(d[46]),"+f"(d[47]),"+f"(d[48]),"+f"(d[49]),"+f"(d[50]),"+f"(d[51]),"+f"(d[52]),"+f"(d[53]),"+f"(d[54]),"+f"(d[55]),"+f"(d[56]),"+f"(d[57]),"+f"(d[58]),"+f"(d[59])
    : "r"(a0), "r"(a1), "r"(a2), "r"(a3), "l"(db), "r"(sd), "n"(TB));
}
template<int TB> __device__ __forceinline__ void wgmma_rs_n128(float (&d)[64], uint32_t a0, uint32_t a1, uint32_t a2, uint32_t a3, uint64_t db, int sd) {
  asm volatile("{\n.reg .pred p;\nsetp.ne.b32 p, %69, 0;\n"
    "wgmma.mma_async.sync.aligned.m64n128k16.f32.bf16.bf16 "
    "{%0,%1,%2,%3,%4,%5,%6,%7,%8,%9,%10,%11,%12,%13,%14,%15,%16,%17,%18,%19,%20,%21,%22,%23,%24,%25,%26,%27,%28,%29,%30,%31,%32,%33,%34,%35,%36,%37,%38,%39,%40,%41,%42,%43,%44,%45,%46,%47,%48,%49,%50,%51,%52,%53,%54,%55,%56,%57,%58,%59,%60,%61,%62,%63}, "
    "{%64,%65,%66,%67}, %68, p, 1, 1, %70;\n}\n"
    : "+f"(d[0]),"+f"(d[1]),"+f"(d[2]),"+f"(d[3]),"+f"(d[4]),"+f"(d[5]),"+f"(d[6]),"+f"(d[7]),"+f"(d[8]),"+f"(d[9]),"+f"(d[10]),"+f"(d[11]),"+f"(d[12]),"+f"(d[13]),"+f"(d[14]),"+f"(d[15]),"+f"(d[16]),"+f"(d[17]),"+f"(d[18]),"+f"(d[19]),"+f"(d[20]),"+f"(d[21]),"+f"(d[22]),"+f"(d[23]),"+f"(d[24]),"+f"(d[25]),"+f"(d[26]),"+f"(d[27]),"+f"(d[28]),"+f"(d[29]),"+f"(d[30]),"+f"(d[31]),"+f"(d[32]),"+f"(d[33]),"+f"(d[34]),"+f"(d[35]),"+f"(d[36]),"+f"(d[37]),"+f"(d[38]),"+f"(d[39]),"+f"(d[40]),"+f"(d[41]),"+f"(d[42]),"+f"(d[43]),"+f"(d[44]),"+f"(d[45]),"+f"(d[46]),"+f"(d[47]),"+f"(d[48]),"+f"(d[49]),"+f"(d[50]),"+f"(d[51]),"+f"(d[52]),"+f"(d[53]),"+f"(d[54]),"+f"(d[55]),"+f"(d[56]),"+f"(d[57]),"+f"(d[58]),"+f"(d[59]),"+f"(d[60]),"+f"(d[61]),"+f"(d[62]),"+f"(d[63])
    : "r"(a0), "r"(a1), "r"(a2), "r"(a3), "l"(db), "r"(sd), "n"(TB));
}
__device__ __forceinline__ void wgmma_ss(float (&d)[40], uint64_t da, uint64_t db, int sd) {
  asm volatile("{\n.reg .pred p;\nsetp.ne.b32 p, %42, 0;\n"
    "wgmma.mma_async.sync.aligned.m64n80k16.f32.bf16.bf16 "
    "{%0,%1,%2,%3,%4,%5,%6,%7,%8,%9,%10,%11,%12,%13,%14,%15,%16,%17,%18,%19,%20,%21,%22,%23,%24,%25,%26,%27,%28,%29,%30,%31,%32,%33,%34,%35,%36,%37,%38,%39}, "
    "%40, %41, p, 1, 1, 0, 1;\n}\n"
    : "+f"(d[0]),"+f"(d[1]),"+f"(d[2]),"+f"(d[3]),"+f"(d[4]),"+f"(d[5]),"+f"(d[6]),"+f"(d[7]),"+f"(d[8]),"+f"(d[9]),"+f"(d[10]),"+f"(d[11]),"+f"(d[12]),"+f"(d[13]),"+f"(d[14]),"+f"(d[15]),"+f"(d[16]),"+f"(d[17]),"+f"(d[18]),"+f"(d[19]),"+f"(d[20]),"+f"(d[21]),"+f"(d[22]),"+f"(d[23]),"+f"(d[24]),"+f"(d[25]),"+f"(d[26]),"+f"(d[27]),"+f"(d[28]),"+f"(d[29]),"+f"(d[30]),"+f"(d[31]),"+f"(d[32]),"+f"(d[33]),"+f"(d[34]),"+f"(d[35]),"+f"(d[36]),"+f"(d[37]),"+f"(d[38]),"+f"(d[39])
    : "l"(da), "l"(db), "r"(sd));
}
__device__ __forceinline__ void wgmma_ss(float (&d)[56], uint64_t da, uint64_t db, int sd) {
  asm volatile("{\n.reg .pred p;\nsetp.ne.b32 p, %58, 0;\n"
    "wgmma.mma_async.sync.aligned.m64n112k16.f32.bf16.bf16 "
    "{%0,%1,%2,%3,%4,%5,%6,%7,%8,%9,%10,%11,%12,%13,%14,%15,%16,%17,%18,%19,%20,%21,%22,%23,%24,%25,%26,%27,%28,%29,%30,%31,%32,%33,%34,%35,%36,%37,%38,%39,%40,%41,%42,%43,%44,%45,%46,%47,%48,%49,%50,%51,%52,%53,%54,%55}, "
    "%56, %57, p, 1, 1, 0, 1;\n}\n"
    : "+f"(d[0]),"+f"(d[1]),"+f"(d[2]),"+f"(d[3]),"+f"(d[4]),"+f"(d[5]),"+f"(d[6]),"+f"(d[7]),"+f"(d[8]),"+f"(d[9]),"+f"(d[10]),"+f"(d[11]),"+f"(d[12]),"+f"(d[13]),"+f"(d[14]),"+f"(d[15]),"+f"(d[16]),"+f"(d[17]),"+f"(d[18]),"+f"(d[19]),"+f"(d[20]),"+f"(d[21]),"+f"(d[22]),"+f"(d[23]),"+f"(d[24]),"+f"(d[25]),"+f"(d[26]),"+f"(d[27]),"+f"(d[28]),"+f"(d[29]),"+f"(d[30]),"+f"(d[31]),"+f"(d[32]),"+f"(d[33]),"+f"(d[34]),"+f"(d[35]),"+f"(d[36]),"+f"(d[37]),"+f"(d[38]),"+f"(d[39]),"+f"(d[40]),"+f"(d[41]),"+f"(d[42]),"+f"(d[43]),"+f"(d[44]),"+f"(d[45]),"+f"(d[46]),"+f"(d[47]),"+f"(d[48]),"+f"(d[49]),"+f"(d[50]),"+f"(d[51]),"+f"(d[52]),"+f"(d[53]),"+f"(d[54]),"+f"(d[55])
    : "l"(da), "l"(db), "r"(sd));
}
__device__ __forceinline__ void wgmma_ss(float (&d)[60], uint64_t da, uint64_t db, int sd) {
  asm volatile("{\n.reg .pred p;\nsetp.ne.b32 p, %62, 0;\n"
    "wgmma.mma_async.sync.aligned.m64n120k16.f32.bf16.bf16 "
    "{%0,%1,%2,%3,%4,%5,%6,%7,%8,%9,%10,%11,%12,%13,%14,%15,%16,%17,%18,%19,%20,%21,%22,%23,%24,%25,%26,%27,%28,%29,%30,%31,%32,%33,%34,%35,%36,%37,%38,%39,%40,%41,%42,%43,%44,%45,%46,%47,%48,%49,%50,%51,%52,%53,%54,%55,%56,%57,%58,%59}, "
    "%60, %61, p, 1, 1, 0, 1;\n}\n"
    : "+f"(d[0]),"+f"(d[1]),"+f"(d[2]),"+f"(d[3]),"+f"(d[4]),"+f"(d[5]),"+f"(d[6]),"+f"(d[7]),"+f"(d[8]),"+f"(d[9]),"+f"(d[10]),"+f"(d[11]),"+f"(d[12]),"+f"(d[13]),"+f"(d[14]),"+f"(d[15]),"+f"(d[16]),"+f"(d[17]),"+f"(d[18]),"+f"(d[19]),"+f"(d[20]),"+f"(d[21]),"+f"(d[22]),"+f"(d[23]),"+f"(d[24]),"+f"(d[25]),"+f"(d[26]),"+f"(d[27]),"+f"(d[28]),"+f"(d[29]),"+f"(d[30]),"+f"(d[31]),"+f"(d[32]),"+f"(d[33]),"+f"(d[34]),"+f"(d[35]),"+f"(d[36]),"+f"(d[37]),"+f"(d[38]),"+f"(d[39]),"+f"(d[40]),"+f"(d[41]),"+f"(d[42]),"+f"(d[43]),"+f"(d[44]),"+f"(d[45]),"+f"(d[46]),"+f"(d[47]),"+f"(d[48]),"+f"(d[49]),"+f"(d[50]),"+f"(d[51]),"+f"(d[52]),"+f"(d[53]),"+f"(d[54]),"+f"(d[55]),"+f"(d[56]),"+f"(d[57]),"+f"(d[58]),"+f"(d[59])
    : "l"(da), "l"(db), "r"(sd));
}


constexpr int PH_WO = 1, PH_W1 = 2, PH_W2 = 4, PH_QKV = 8;
constexpr int SA = 4, SB = 10, STAGE = 16384;
constexpr int SM_B = SA * STAGE;
constexpr int SM_CS = SM_B + SB * STAGE;
constexpr int SM_B1 = SM_CS + 448;
constexpr int SM_ROW = SM_B1 + 224;
constexpr int SM_BAR = SM_ROW + 2048;
constexpr int CHAIN_SMEM = SM_BAR + 344;
static_assert(CHAIN_SMEM <= 232448, "shared memory");
constexpr int CHAIN_THREADS = 352;
constexpr int BAR_FA = 0, BAR_EA = SA * 8, BAR_FB = 2 * SA * 8, BAR_EB = (2 * SA + SB) * 8, BAR_AUX = (2 * SA + 2 * SB) * 8, BAR_JOB = BAR_AUX + 32,
              BAR_FH = BAR_JOB, BAR_EH = BAR_JOB + 40, BAR_TILE = BAR_JOB + 80;

struct alignas(64) ChainParams {
  CUtensorMap a_x, b_wo, b_w1, b_wqkv, o_out;
  const bf16* xres;
  const bf16* xin;
  const bf16 *b1, *b2;
  unsigned int* flags;
  signed char pref[160];
};

template <int V> struct IC { static constexpr int value = V; };
struct Ring { uint32_t s, ph; };
template <int N> __device__ __forceinline__ void ring_adv(Ring& r) { if (++r.s == N) { r.s = 0; r.ph ^= 1; } }

template <int N, int STRIDE>
__device__ __forceinline__ void produce(int n, uint32_t bytes, uint32_t lim, const uint8_t* src, uint32_t dst, uint32_t full, uint32_t empty, Ring& r) {
#pragma unroll 1
  for (int kt = 0; kt < n; kt++) {
    if (lim) mbar_wait(full + (r.s >= lim ? r.s - lim : r.s + N - lim) * 8, r.s >= lim ? r.ph : r.ph ^ 1);
    mbar_wait(empty + r.s * 8, r.ph ^ 1);
    mbar_expect_tx(full + r.s * 8, bytes);
    bulk_g2s(dst + r.s * STRIDE, src + kt * bytes, bytes, full + r.s * 8);
    ring_adv<N>(r);
  }
}
__device__ __forceinline__ void bulk_s2g(void* dst, uint32_t src, uint32_t bytes) {
  asm volatile("cp.async.bulk.global.shared::cta.bulk_group [%0], [%1], %2;\ncp.async.bulk.commit_group;" ::"l"(dst), "r"(src), "r"(bytes) : "memory");
}
template <int BK, bool B128> __device__ __forceinline__ uint64_t b_desc(uint32_t addr) { return B128 ? mk_desc(addr, 8192, 1024, 1) : mk_desc(addr, BK * 32, 256, 3); }

template <int BN, int MT, int BK, int APT, bool TILED, bool B128, bool HR = false>
__device__ __forceinline__ void mainloop(float (&acc)[MT][BN / 2], uint32_t sbase, uint32_t bars, int lane, int wg, int KT, int a0, bool pass, Ring& rb, int cont = 0) {
  constexpr int NA = HR ? 5 : SA, AST = HR ? 12288 : STAGE, FA = HR ? BAR_FH : BAR_FA, EA = HR ? BAR_EH : BAR_EA;
  Ring ra{(uint32_t)a0 % NA, ((uint32_t)a0 / NA) & 1};
#pragma unroll
  for (int m = 0; m < MT; m++) fence_regs(acc[m]);
  if (HR || a0 != 0) named_bar(6 - wg, 256);
  mbar_wait(bars + BAR_FB + rb.s * 8, rb.ph);
  mbar_wait(bars + FA + ra.s * 8, ra.ph);
  const uint64_t da0 = TILED ? mk_desc(sbase, 128, BK * 16, 0) : mk_desc(sbase, 16, 1024, 1), db0 = b_desc<BK, B128>(sbase + SM_B);
  constexpr int NS = BK / 16, H = MT == 2 ? 1 : 2, KA = TILED ? 16 : 2, KB = B128 ? 128 : 32;
  uint32_t relA = 0, relB = 0;
  uint64_t da = da0 + ra.s * (AST / 16), db = db0 + rb.s * (STAGE / 16);
  auto part = [&](auto k0, auto k1, int sd) {
#pragma unroll
    for (int k = k0.value; k < k1.value; k++)
#pragma unroll
      for (int m = 0; m < MT; m++) wgmma_ss(acc[m], da + m * 512 + k * KA, db + k * KB, k == 0 ? sd : 1);
    wg_commit();
  };
  wg_fence();
  part(IC<0>{}, IC<H>{}, cont);
#pragma unroll 1
  for (int kt = 0; kt < KT - 1; kt++) {
    const bool adv = APT == 1 || (kt & 1);
    const uint32_t curA = adv ? bars + EA + ra.s * 8 : 0, curB = bars + BAR_EB + rb.s * 8;
    if (adv) ring_adv<NA>(ra);
    ring_adv<SB>(rb);
    const uint64_t na = adv ? da0 + ra.s * (AST / 16) : da + 512, nb = db0 + rb.s * (STAGE / 16);
    const bool ok = mbar_test(bars + BAR_FB + rb.s * 8, rb.ph) & mbar_test(bars + FA + ra.s * 8, ra.ph);
    wg_wait<1>();
    mbar_arrive_if(relA, lane == 0 && relA);
    mbar_arrive_if(relB, lane == 0 && relB);
    wg_fence();
    part(IC<H>{}, IC<NS>{}, 1);
    relA = curA; relB = curB; da = na; db = nb;
    if (!ok) {
      mbar_wait(bars + BAR_FB + rb.s * 8, rb.ph);
      mbar_wait(bars + FA + ra.s * 8, ra.ph);
    }
    wg_fence();
    part(IC<0>{}, IC<H>{}, 1);
  }
  if (pass) asm volatile("bar.arrive %0, 256;" ::"r"(5 + wg) : "memory");
  wg_wait<1>();
  mbar_arrive_if(relA, lane == 0 && relA);
  mbar_arrive_if(relB, lane == 0);
  wg_fence();
  part(IC<H>{}, IC<NS>{}, 1);
  relA = bars + EA + ra.s * 8; relB = bars + BAR_EB + rb.s * 8;
  ring_adv<SB>(rb);
  wg_wait<0>();
#pragma unroll
  for (int m = 0; m < MT; m++) fence_regs(acc[m]);
  if (lane == 0) { mbar_arrive(relA); mbar_arrive(relB); }
}
__device__ __forceinline__ void acquire_stage(uint32_t bars, const Ring& rb, uint32_t s) { mbar_wait(bars + BAR_EB + s * 8, s >= rb.s ? rb.ph ^ 1 : rb.ph); }

template <bool FINAL>
__device__ __forceinline__ void epi_resid(const float (&acc)[40], uint32_t (&res)[20], bf16* out, float2* st, uint8_t* stage, int row0, int j, int lane) {
  const int q = lane & 3;
  uint32_t* o0 = FINAL ? (uint32_t*)(stage + (row0 & 63) * 160) + q : (uint32_t*)out + lane;
  float s0 = 0.f, t0 = 0.f, s1 = 0.f, t1 = 0.f;
#pragma unroll
  for (int b = 0; b < 10; b++) {
    res[2 * b] = pack_bf16(acc[4 * b], acc[4 * b + 1]);
    res[2 * b + 1] = pack_bf16(acc[4 * b + 2], acc[4 * b + 3]);
    if (FINAL) { o0[b * 4] = res[2 * b]; o0[b * 4 + 320] = res[2 * b + 1]; }
    else { const int ln = x_line(row0, j * 10 + b); o0[ln * 32] = res[2 * b]; o0[ln * 32 + 256] = res[2 * b + 1]; }
  }
  if (!FINAL) {
#pragma unroll
    for (int b = 0; b < 10; b++) {
      s0 += acc[4 * b] + acc[4 * b + 1]; t0 = fmaf(acc[4 * b], acc[4 * b], fmaf(acc[4 * b + 1], acc[4 * b + 1], t0));
      s1 += acc[4 * b + 2] + acc[4 * b + 3]; t1 = fmaf(acc[4 * b + 2], acc[4 * b + 2], fmaf(acc[4 * b + 3], acc[4 * b + 3], t1));
    }
#pragma unroll
    for (int m = 1; m < 4; m <<= 1) {
      s0 += __shfl_xor_sync(0xffffffffu, s0, m); t0 += __shfl_xor_sync(0xffffffffu, t0, m);
      s1 += __shfl_xor_sync(0xffffffffu, s1, m); t1 += __shfl_xor_sync(0xffffffffu, t1, m);
    }
    if (q < 2) st[j * SEQ + row0 + q * 8] = q ? make_float2(s1, t1) : make_float2(s0, t0);
  }
}
__device__ __forceinline__ void publish(unsigned int* f, int wg, int tid) {
  named_bar(2 + wg, 128);
  if ((tid & 127) == 0) flag_signal(f);
}
__device__ __forceinline__ float gelu_half(float s) {
  const float z = s * fmaf(s * s, 8.f * 0.044715f * 0.7978845608028654f, 2.f * 0.7978845608028654f);
  float th;
  asm("tanh.approx.f32 %0, %1;" : "=f"(th) : "f"(z));
  return fmaf(s, th, s);
}
template <bool DOUBLE> __device__ __forceinline__ float2 row_coef(float s, float t) {
  const float mean = s * (1.f / DM);
  const float var = fmaxf(fmaf(-mean, mean, t * (1.f / DM)), 0.f);
  float r = rsqrtf(var + LN_EPS);
  if (DOUBLE) r *= 0.5f * rsqrtf(var * r * r + LN_EPS);
  return make_float2(r, -r * mean);
}
template <bool DOUBLE, int NP> __device__ __forceinline__ void reduce_stats(const float2* st, float2* dst, int i, int lane) {
  float4 v[2][NP];
#pragma unroll
  for (int rr = 0; rr < 2; rr++)
#pragma unroll
    for (int k = 0; k < NP; k++) v[rr][k] = __ldcg((const float4*)(st + k * SEQ + i * 128 + rr * 64) + lane);
#pragma unroll
  for (int rr = 0; rr < 2; rr++) {
    float s0 = 0.f, t0 = 0.f, s1 = 0.f, t1 = 0.f;
#pragma unroll
    for (int k = 0; k < NP; k++) { s0 += v[rr][k].x; t0 += v[rr][k].y; s1 += v[rr][k].z; t1 += v[rr][k].w; }
    dst[rr * 64 + lane * 2] = row_coef<DOUBLE>(s0, t0);
    dst[rr * 64 + lane * 2 + 1] = row_coef<DOUBLE>(s1, t1);
  }
}

template <int PH, bool FIRST, bool LAST>
__global__ void __launch_bounds__(CHAIN_THREADS, 1) chain_kernel(const __grid_constant__ ChainParams p) {
  extern __shared__ __align__(1024) uint8_t smem[];
  const uint32_t sbase = smem_u32(smem), bars = sbase + SM_BAR;
  float* cs = (float*)(smem + SM_CS);
  uint32_t* sb1 = (uint32_t*)(smem + SM_B1);
  const int tid = threadIdx.x, lane = tid & 31, warp = __shfl_sync(0xffffffffu, tid >> 5, 0);
  if (tid == 32) {
    unsigned int* claim = p.flags + 64;
    uint32_t smid;
    asm volatile("mov.u32 %0, %%smid;" : "=r"(smid));
    int t = smid < 160 ? p.pref[smid] : -1;
    if (t >= 0 && atomicExch(claim + t, 1u) != 0u) t = -2;
    if (t == -1) {
#pragma unroll 1
      for (int it = 0; it < 100000; it++) {
        if (*(volatile unsigned int*)(claim + 128) >= 128u) break;
        __nanosleep(200);
      }
    }
    if (t < 0) {
      t = -1;
      if (*(volatile unsigned int*)(claim + 128) < 128u) {
#pragma unroll 1
        for (int c = 0; c < 128 && t < 0; c++)
          if (atomicExch(claim + c, 1u) == 0u) t = c;
      }
    }
    if (t >= 0) atomicAdd(claim + 128, 1u);
    *(volatile int*)(smem + SM_BAR + BAR_TILE) = t;
  }
  unsigned int* fl = p.flags;
  if (tid == 0) {
    for (int s = 0; s < SA; s++) { mbar_init(bars + BAR_FA + s * 8, 1); mbar_init(bars + BAR_EA + s * 8, 4); }
    for (int s = 0; s < SB; s++) { mbar_init(bars + BAR_FB + s * 8, 1); mbar_init(bars + BAR_EB + s * 8, 8); }
    mbar_init(bars + BAR_AUX, 32); mbar_init(bars + BAR_AUX + 8, 32);
    mbar_init(bars + BAR_AUX + 16, FIRST ? 37 : 32); mbar_init(bars + BAR_AUX + 24, 32);
    for (int s = 0; s < 5; s++) { mbar_init(bars + BAR_FH + s * 8, 1); mbar_init(bars + BAR_EH + s * 8, 4); }
    asm volatile("fence.mbarrier_init.release.cluster;" ::: "memory");
  }
  if (tid == 256) {
    if (FIRST) {
      uint32_t smid;
      asm volatile("mov.u32 %0, %%smid;" : "=r"(smid));
      const int t = smid < 160 ? p.pref[smid] : -1;
      if (t >= 0) {
        asm volatile("cp.async.bulk.prefetch.tensor.2d.L2.global [%0, {%1, %2}];" ::"l"(&p.a_x), "r"(0), "r"((t >> 4) * 256) : "memory");
        asm volatile("cp.async.bulk.prefetch.tensor.3d.L2.global [%0, {%1, %2, %3}];" ::"l"(&p.b_wqkv), "r"(0), "r"(t & 15), "r"(0) : "memory");
        asm volatile("cp.async.bulk.prefetch.tensor.3d.L2.global [%0, {%1, %2, %3}];" ::"l"(&p.b_wqkv), "r"(64), "r"(t & 15), "r"(0) : "memory");
      }
      prefetch_map(&p.b_w1); prefetch_map(&p.b_wo);
    }
    if (LAST) prefetch_map(&p.o_out);
  }
  __syncthreads();
  pdl_launch();
  const int tile = *(volatile int*)(smem + SM_BAR + BAR_TILE);
  if (tile < 0) return;
  const int g = tile >> 4, c = tile & 15;

  if (warp == 9) {
    if (lane == 0) {
      if (FIRST) {
#pragma unroll 1
        for (int kt = 0; kt < 10; kt++) {
          if (kt >= 3) mbar_wait(bars + BAR_FB + (kt - 3) * 8, 0);
          mbar_expect_tx(bars + BAR_FB + kt * 8, STAGE);
          tma_3d(sbase + SM_B + kt * STAGE, &p.b_wqkv, 0, c, kt * 64, bars + BAR_FB + kt * 8);
          tma_3d(sbase + SM_B + kt * STAGE + 8192, &p.b_wqkv, 64, c, kt * 64, bars + BAR_FB + kt * 8);
        }
#pragma unroll 1
        for (int kt = g; kt < 10; kt += 8) {
          mbar_wait(bars + BAR_FB + kt * 8, 0);
          bulk_s2g(g_wt + WT_QKV + (c * 10 + kt) * STAGE, sbase + SM_B + kt * STAGE, STAGE);
        }
        asm volatile("cp.async.bulk.wait_group.read 0;" ::: "memory");
        mbar_arrive(bars + BAR_AUX + 16);
        asm volatile("cp.async.bulk.wait_group 0;" ::: "memory");
      } else {
        Ring r{0, 0};
#pragma unroll 1
        for (int ph = 0; ph < ((PH & PH_QKV) ? 4 : 3); ph++) {
          if (ph == 2) pdl_wait();
          const uint32_t bytes = ph == 0 ? 10240 : (ph == 1 ? 14336 : (ph == 2 ? 15360 : STAGE));
          const int n = ph == 2 ? 18 : 10, off = ph == 0 ? WT_WO : (ph == 1 ? WT_W1 : (ph == 2 ? WT_W2 : WT_QKV));
          produce<SB, STAGE>(n, bytes, ph == 0 ? 0 : (ph == 2 ? 3 : 2), g_wt + off + ((ph & 1) ? c : c >> 1) * n * bytes, sbase + SM_B, bars + BAR_FB,
                             bars + BAR_EB, r);
        }
      }
    }
  } else if (warp == 8) {
    if (lane == 0) {
      Ring r{0, 0};
      if (FIRST) {
#pragma unroll 1
        for (int t = 0; t < 20; t++) {
          mbar_wait(bars + BAR_EA + r.s * 8, r.ph ^ 1);
          mbar_expect_tx(bars + BAR_FA + r.s * 8, STAGE);
          tma_2d(sbase + r.s * STAGE, &p.a_x, (t % 10) * 64, g * 256 + (t / 10) * 128, bars + BAR_FA + r.s * 8);
          ring_adv<SA>(r);
        }
        mbar_wait(bars + BAR_AUX + 16, 0);
#pragma unroll 1
        for (int job = tile; job < 240; job += 128) {
          const int n = job >> 7;
          mbar_wait(bars + BAR_EB + (3 + n) * 8, 0);
          mbar_expect_tx(bars + BAR_JOB + n * 8, job < 160 ? 14336 : 10240);
#pragma unroll 1
          for (int b = 0; b < (job < 160 ? 7 : 5); b++)
            tma_3d(sbase + SM_B + (3 + n) * STAGE + b * 2048, job < 160 ? &p.b_w1 : &p.b_wo, (job < 160 ? ((job / 10) & 1) * 112 : 0) + b * 16,
                   job < 160 ? job / 20 : job / 10 - 16, (job % 10) * 64, bars + BAR_JOB + n * 8);
        }
#pragma unroll 1
        for (int job = tile; job < 240; job += 128) {
          mbar_wait(bars + BAR_JOB + (job >> 7) * 8, 0);
          bulk_s2g(g_wt + (job < 160 ? WT_W1 + job * 14336 : WT_WO + (job - 160) * 10240), sbase + SM_B + (3 + (job >> 7)) * STAGE, job < 160 ? 14336 : 10240);
        }
        asm volatile("cp.async.bulk.wait_group 0;" ::: "memory");
      } else {
        pdl_wait();
#pragma unroll 1
        for (int ph = 0; ph < ((PH & PH_QKV) ? 3 : 2); ph++) {
#pragma unroll 1
          for (int s = 0; s < 2; s++) {
            if (ph) { flag_wait(fl + (ph - 1) * 32 + g * 2 + s, 16); fence_async_global(); }
            const uint8_t* src = ph == 0 ? (const uint8_t*)g_o + (g * 4 + s * 2 + (c & 1)) * 81920 : (const uint8_t*)(ph == 1 ? g_x1 : g_x2) + (g * 2 + s) * 163840;
            produce<SA, STAGE>(ph ? 10 : 5, 16384, 0, src, sbase, bars + BAR_FA, bars + BAR_EA, r);
          }
          if (ph == 1) {
            Ring rh{0, 0};
#pragma unroll 1
            for (int s = 0; s < SA; s++) mbar_wait(bars + BAR_EA + s * 8, s >= r.s ? r.ph ^ 1 : r.ph);
#pragma unroll 1
            for (int s = 0; s < 4; s++) {
              if (s < 2) { flag_wait(fl + 16 + g * 2 + s, 16); fence_async_global(); }
              produce<5, 12288>(s < 2 ? 10 : 8, 12288, 0, (const uint8_t*)g_h + ((g * 4 + (s & 1) * 2 + (c & 1)) * 18 + (s >> 1) * 10) * 12288, sbase, bars + BAR_FH,
                                bars + BAR_EH, rh);
            }
#pragma unroll 1
            for (int s = 0; s < 5; s++) mbar_wait(bars + BAR_EH + s * 8, s >= rh.s ? rh.ph ^ 1 : rh.ph);
          }
        }
      }
    }
  } else if (warp == 10) {
    float2* srow = (float2*)(smem + SM_ROW);
    if (FIRST) {
      named_bar(4, 160);
      if (lane == 0) flag_signal(fl + g * 2 + (c >> 3));
#pragma unroll 1
      for (int s = 0; s < 2; s++) {
        if (lane == 0) flag_wait(fl + g * 2 + s, 8);
        __syncwarp();
        reduce_stats<false, 2>(g_s.st0, srow + s * 128, g * 2 + s, lane);
        mbar_arrive(bars + BAR_AUX + 16 + s * 8);
      }
#pragma unroll 1
      for (int n = 0; n < 2; n++) {
        const int job = n * 128 + tile;
        if (job < 160) {
          mbar_wait(bars + BAR_JOB + n * 8, 0);
          const uint8_t* base = smem + SM_B + (3 + n) * STAGE + ((lane & 15) >> 1) * 2048 + (lane >> 4) * 1024;
          float a[8];
#pragma unroll
          for (int e = 0; e < 8; e++) a[e] = 0.f;
#pragma unroll 4
          for (int r = 0; r < 32; r++) {
            const uint4 v = *(const uint4*)(base + r * 32 + (((lane & 1) ^ ((r >> 2) & 1)) * 16));
            a[0] += bf_lo(v.x); a[1] += bf_hi(v.x); a[2] += bf_lo(v.y); a[3] += bf_hi(v.y);
            a[4] += bf_lo(v.z); a[5] += bf_hi(v.z); a[6] += bf_lo(v.w); a[7] += bf_hi(v.w);
          }
#pragma unroll
          for (int e = 0; e < 8; e++) a[e] += __shfl_xor_sync(0xffffffffu, a[e], 16);
          if (lane < 14) {
            float4* d = (float4*)(g_s.csp_w1 + (job % 10) * 1792 + (job / 10) * 112 + lane * 8);
            d[0] = make_float4(a[0], a[1], a[2], a[3]); d[1] = make_float4(a[4], a[5], a[6], a[7]);
          }
        }
      }
    } else {
      if (lane < 28) {
        float4 v[10], a = make_float4(0.f, 0.f, 0.f, 0.f);
#pragma unroll
        for (int k = 0; k < 10; k++) v[k] = __ldcg((const float4*)(g_s.csp_w1 + k * 1792 + c * 112) + lane);
#pragma unroll
        for (int k = 0; k < 10; k++) { a.x += v[k].x; a.y += v[k].y; a.z += v[k].z; a.w += v[k].w; }
        ((float4*)cs)[lane] = a;
      }
      for (int k = lane; k < 56; k += 32) {
        const int col = (c >> 1) * 216 + (c & 1) * 112 + k * 2;
        const uint32_t v = col < FF ? __ldg((const uint32_t*)(p.b1 + col)) : 0u;
        sb1[k] = pack_bf16(0.5f * bf_lo(v), 0.5f * bf_hi(v));
      }
#pragma unroll 1
      for (int s = 0; s < 2; s++) {
        if (lane == 0) flag_wait(fl + g * 2 + s, 16);
        __syncwarp();
        reduce_stats<true, 8>(g_s.st1, srow + s * 128, g * 2 + s, lane);
        mbar_arrive(bars + BAR_AUX + s * 8);
      }
      if (PH & PH_QKV) {
        const float4 cq = lane < 30 ? __ldcg((const float4*)(g_s.cs_qkv + c * 120) + lane) : make_float4(0.f, 0.f, 0.f, 0.f);
#pragma unroll 1
        for (int s = 0; s < 2; s++) {
          if (lane == 0) { if (s == 0) flag_wait(fl + 16 + g * 2 + 1, 16); flag_wait(fl + 32 + g * 2 + s, 16); }
          __syncwarp();
          if (s == 0 && lane < 30) ((float4*)cs)[lane] = cq;
          reduce_stats<false, 8>(g_s.st2, srow + s * 128, g * 2 + s, lane);
          mbar_arrive(bars + BAR_AUX + 16 + s * 8);
        }
      }
    }
  } else {
    const int wg = warp >> 2, w4 = warp & 3, q = lane & 3;
    const int rbk = g * 2 + wg, rl = w4 * 16 + (lane >> 2);
    const int rowS = rbk * 128 + (c & 1) * 64 + rl, jS = c >> 1;
    const float2* srow = (const float2*)(smem + SM_ROW) + wg * 128;
    const bool t0 = (tid & 127) == 0;
    Ring rb{0, 0};
    uint32_t res[20];
    if (FIRST) {
      if (wg == 1) {
        const int xrow = g * 256 + c * 16 + (w4 & 1) * 8 + (lane >> 2), xcg = (w4 >> 1) * 40 + q;
        uint4 xv[10];
#pragma unroll
        for (int k = 0; k < 10; k++) xv[k] = __ldg((const uint4*)(p.xin + (size_t)xrow * DM) + xcg + k * 4);
        float xs = 0.f, xt = 0.f;
#pragma unroll
        for (int k = 0; k < 10; k++) {
          const uint32_t e[4] = {xv[k].x, xv[k].y, xv[k].z, xv[k].w};
#pragma unroll
          for (int m = 0; m < 4; m++) { const float a = bf_lo(e[m]), b = bf_hi(e[m]); xs += a + b; xt = fmaf(a, a, fmaf(b, b, xt)); }
        }
#pragma unroll
        for (int m = 1; m < 4; m <<= 1) { xs += __shfl_xor_sync(0xffffffffu, xs, m); xt += __shfl_xor_sync(0xffffffffu, xt, m); }
        if (q == 0) g_s.st0[(w4 >> 1) * SEQ + xrow] = make_float2(xs, xt);
        asm volatile("bar.arrive 4, 160;" ::: "memory");
#pragma unroll
        for (int k = 0; k < 10; k++) *((uint4*)g_x0 + x_line(xrow, xcg + k * 4) * 8 + (xrow & 7)) = xv[k];
        float o[60];
        const uint32_t one = 0x3F803F80u;
#pragma unroll 1
        for (int kt = 0; kt < 10; kt++) {
          mbar_wait(bars + BAR_FB + kt * 8, 0);
          wg_fence();
#pragma unroll
          for (int k = 0; k < 4; k++) wgmma_rs_n120<1>(o, one, one, one, one, b_desc<64, true>(sbase + SM_B + kt * STAGE) + k * 128, (kt | k) != 0);
          wg_commit();
        }
        wg_wait<0>();
        fence_regs(o);
        if ((tid & 127) < 4) {
#pragma unroll
          for (int b = 0; b < 15; b++) {
            *(float2*)(cs + b * 8 + q * 2) = make_float2(o[4 * b], o[4 * b + 1]);
            if (g == 0) *(float2*)(g_s.cs_qkv + c * 120 + b * 8 + q * 2) = make_float2(o[4 * b], o[4 * b + 1]);
          }
          mbar_arrive(bars + BAR_AUX + 16);
        }
        named_bar(3, 128);
      }
    } else {
#pragma unroll
      for (int b = 0; b < 10; b++) {
        const uint32_t* r0 = (const uint32_t*)p.xres + x_line(rowS, jS * 10 + b) * 32 + lane;
        res[2 * b] = __ldcg(r0); res[2 * b + 1] = __ldcg(r0 + 256);
      }
      {
        float acc[1][40];
#pragma unroll
        for (int b = 0; b < 20; b++) { acc[0][2 * b] = bf_lo(res[b]); acc[0][2 * b + 1] = bf_hi(res[b]); }
        mainloop<80, 1, 64, 2, true, false>(acc, sbase, bars, lane, wg, 10, wg * 5, wg != 0, rb, 1);
        epi_resid<false>(acc[0], res, g_x1, g_s.st1, smem, rowS, jS, lane);
        if (wg == 0) asm volatile("bar.arrive 5, 256;" ::: "memory");
        publish(fl + rbk, wg, tid);
      }
      {
        float acc[2][56];
        mainloop<112, 2, 64, 1, true, false>(acc, sbase, bars, lane, wg, 10, 10 + wg * 10, true, rb);
        mbar_wait(bars + BAR_AUX + wg * 8, 0);
        const float2 c0 = srow[rl], c1 = srow[rl + 8], c2 = srow[rl + 64], c3 = srow[rl + 72];
        const int cg0 = (c >> 1) * 27 + (c & 1) * 14;
        uint32_t* o0 = (uint32_t*)g_h + h_line(rbk * 128 + rl, cg0) * 32 + lane;
        int kg = cg0 % 12;
#pragma unroll
        for (int b = 0; b < 14; b++) {
          if (b < 13 || !(c & 1)) {
            const float2 cc = *(const float2*)(cs + b * 8 + q * 2);
            const uint32_t bb = sb1[b * 4 + q];
            const float bl = bf_lo(bb), bh = bf_hi(bb);
            o0[0] = pack_bf16(gelu_half(fmaf(c0.x, acc[0][4 * b], fmaf(c0.y, cc.x, bl))), gelu_half(fmaf(c0.x, acc[0][4 * b + 1], fmaf(c0.y, cc.y, bh))));
            o0[384] = pack_bf16(gelu_half(fmaf(c1.x, acc[0][4 * b + 2], fmaf(c1.y, cc.x, bl))), gelu_half(fmaf(c1.x, acc[0][4 * b + 3], fmaf(c1.y, cc.y, bh))));
            o0[18 * 3072] = pack_bf16(gelu_half(fmaf(c2.x, acc[1][4 * b], fmaf(c2.y, cc.x, bl))), gelu_half(fmaf(c2.x, acc[1][4 * b + 1], fmaf(c2.y, cc.y, bh))));
            o0[18 * 3072 + 384] = pack_bf16(gelu_half(fmaf(c3.x, acc[1][4 * b + 2], fmaf(c3.y, cc.x, bl))), gelu_half(fmaf(c3.x, acc[1][4 * b + 3], fmaf(c3.y, cc.y, bh))));
            o0 += (++kg == 12) ? (96 - 11) * 32 : 32;
            if (kg == 12) kg = 0;
          }
        }
        publish(fl + 16 + rbk, wg, tid);
      }
      {
        float acc[1][40];
#pragma unroll
        for (int b = 0; b < 10; b++) {
          const uint32_t bb = __ldg((const uint32_t*)(p.b2 + jS * 80) + b * 4 + q);
          acc[0][4 * b] = bf_lo(res[2 * b]) + bf_lo(bb); acc[0][4 * b + 1] = bf_hi(res[2 * b]) + bf_hi(bb);
          acc[0][4 * b + 2] = bf_lo(res[2 * b + 1]) + bf_lo(bb); acc[0][4 * b + 3] = bf_hi(res[2 * b + 1]) + bf_hi(bb);
        }
#pragma unroll 1
        for (int sg = 0; sg < 2; sg++)
          mainloop<80, 1, 96, 1, true, false, true>(acc, sbase, bars, lane, wg, sg ? 8 : 10, sg ? 20 + wg * 8 : wg * 10, !sg || (LAST ? wg == 0 : wg != 0), rb, 1);
        if (LAST) {
          const uint32_t st = (rb.s + wg) % SB;
          acquire_stage(bars, rb, st);
          epi_resid<true>(acc[0], res, nullptr, nullptr, smem + SM_B + st * STAGE, rowS, jS, lane);
          asm volatile("fence.proxy.async.shared::cta;" ::: "memory");
          named_bar(2 + wg, 128);
          if (t0) {
            asm volatile("cp.async.bulk.tensor.2d.global.shared::cta.bulk_group [%0, {%2, %3}], [%1];" ::"l"(&p.o_out), "r"(sbase + SM_B + st * STAGE), "r"(jS * 80),
                         "r"(rbk * 128 + (c & 1) * 64) : "memory");
            asm volatile("cp.async.bulk.commit_group;\ncp.async.bulk.wait_group 0;" ::: "memory");
          }
        } else {
          epi_resid<false>(acc[0], res, g_x2, g_s.st2, smem, rowS, jS, lane);
          if (wg == 0) asm volatile("bar.arrive 5, 256;" ::: "memory");
          publish(fl + 32 + rbk, wg, tid);
        }
      }
    }
    if (PH & PH_QKV) {
      float acc[2][60];
      mainloop<120, 2, 64, 1, !FIRST, true>(acc, sbase, bars, lane, wg, 10, (FIRST ? 0 : 30) + wg * 10, wg == 0, rb);
      mbar_wait(bars + BAR_AUX + 16 + wg * 8, 0);
      pdl_wait();
      const float QS = 0.22360679774997896f * 1.4426950408889634f;
      unsigned int* smax = sb1 + 16 + wg * 8;
      if ((tid & 127) < 6) smax[tid & 127] = 0u;
      named_bar(2 + wg, 128);
      int off[5];
#pragma unroll
      for (int m = 0; m < 5; m++) {
        const int cc = m * 8 + q * 2, hh = cc >= 20, d = cc - hh * 20;
        off[m] = hh * 6144 + (d >> 3) * 128 + (d & 7) * 2;
      }
#pragma unroll
      for (int pr = 0; pr < 3; pr++) {
        const int part = (c * 6 + pr * 2) >> 5;
        float nrm[2];
        const uint32_t sst = (rb.s + pr) % SB, soff = wg ? pr * STAGE : SM_B + sst * STAGE;
        if (wg == 0) acquire_stage(bars, rb, sst);
        uint8_t* stg = smem + soff + w4 * 768 + (lane >> 2) * 16;
#pragma unroll
        for (int mt = 0; mt < 2; mt++) {
          const float2 c0 = srow[mt * 64 + rl], c1 = srow[mt * 64 + rl + 8];
          const bool mu0 = is_mufu(mt * 8 + w4 * 2), mu1 = is_mufu(mt * 8 + w4 * 2 + 1), mu = (q & 1) ? mu1 : mu0;
          const float s0 = part == 0 ? QS : (part == 1 && !mu0 ? 0x1p-22f : 1.f), s1 = part == 0 ? QS : (part == 1 && !mu1 ? 0x1p-22f : 1.f);
          const float a0 = c0.x * s0, b0 = c0.y * s0, a1 = c1.x * s1, b1 = c1.y * s1;
          float nA0 = 0.f, nA1 = 0.f, nB0 = 0.f, nB1 = 0.f;
#pragma unroll
          for (int m = 0; m < 5; m++) {
            const int b = pr * 5 + m;
            const float2 cc = *(const float2*)(cs + b * 8 + q * 2);
            uint8_t* ptr = stg + off[m] + mt * 3072;
            const float v0 = fmaf(a0, acc[mt][4 * b], b0 * cc.x), v1 = fmaf(a0, acc[mt][4 * b + 1], b0 * cc.y);
            const float v2 = fmaf(a1, acc[mt][4 * b + 2], b1 * cc.x), v3 = fmaf(a1, acc[mt][4 * b + 3], b1 * cc.y);
            *(uint32_t*)ptr = pack_bf16(v0, v1);
            *(uint32_t*)(ptr + 384) = pack_bf16(v2, v3);
            const float n0 = fmaf(v0, v0, v1 * v1), n1 = fmaf(v2, v2, v3 * v3);
            if (m < 2) { nA0 += n0; nA1 += n1; } else if (m > 2) { nB0 += n0; nB1 += n1; }
            else if (q < 2) { nA0 += n0; nA1 += n1; } else { nB0 += n0; nB1 += n1; }
          }
          const uint2 ex = part == 0 ? make_uint2(0x3F803F80u, 0x00003F80u)
                                     : (part == 1 ? (mu ? make_uint2(0u, 0u) : make_uint2(0x377C3C00u, 0x00003020u)) : make_uint2(0x00003F80u, 0u));
          *(uint2*)(stg + mt * 3072 + (q >> 1) * 6144 + (q & 1) * 384 + 264) = ex;
          float x = (q & 1) ? nA1 : nA0, y = (q & 1) ? nB1 : nB0;
          x += __shfl_xor_sync(0xffffffffu, (q & 1) ? nA0 : nA1, 1);
          y += __shfl_xor_sync(0xffffffffu, (q & 1) ? nB0 : nB1, 1);
          float n = (q & 2) ? y : x;
          n += __shfl_xor_sync(0xffffffffu, (q & 2) ? x : y, 2);
          nrm[mt] = (part == 1 && !mu) ? n * 0x1p44f : n;
        }
        asm volatile("fence.proxy.async.shared::cta;" ::: "memory");
        named_bar(2 + wg, 128);
        if ((tid & 127) < 2) bulk_s2g((uint8_t*)g_qkv + (size_t)(c * 6 + pr * 2 + lane) * HEAD_BYTES + rbk * 6144, sbase + soff + lane * 6144, 6144);
        if (part < 2) atomicMax(smax + pr * 2 + (q >> 1), max(__float_as_uint(nrm[0]) & 0x7FFFFFFFu, __float_as_uint(nrm[1]) & 0x7FFFFFFFu));
      }
      named_bar(2 + wg, 128);
      if ((tid & 127) < 6 && c * 6 + (tid & 127) < 64) atomicMax(fl + NORM_OFF + c * 6 + (tid & 127), smax[tid & 127]);
      if ((tid & 127) < 2) {
        asm volatile("cp.async.bulk.wait_group 0;" ::: "memory");
      }
    }
  }
}

__device__ __forceinline__ uint32_t exp2_poly_pair(float a0, float a1) {
  const uint32_t v = __byte_perm(__float_as_uint(a0), __float_as_uint(a1), 0x7430);
  const uint32_t e = __byte_perm(__float_as_uint(a0), __float_as_uint(a1), 0x6521);
  uint32_t u;
  asm("fma.rn.f16x2 %0, %1, %2, %3;" : "=r"(u) : "r"(v), "r"(0x1d611d61u), "r"(0xa012a012u));
  asm("fma.rn.f16x2 %0, %1, %2, %3;" : "=r"(u) : "r"(u), "r"(v), "r"(0x21622162u));
  uint32_t r;
  asm("{\n.reg .b32 t;\nshl.b32 t, %1, 7;\nadd.u32 %0, t, %2;\n}" : "=r"(r) : "r"(e), "r"(u));
  return r;
}
constexpr int KPITCH = 6144 + 128;
constexpr int ATT_V = 16 * KPITCH, ATT_JOB = ATT_V + HEAD_BYTES, ATT_BAR = ATT_JOB + 2 * 15360, ATT_SMEM = ATT_BAR + 128;

__device__ __forceinline__ void att_store(const float (&O)[12], int row0, int h, int lane) {
  const float l0 = __shfl_sync(0xffffffffu, O[8], (lane & ~3) | 2), l1 = __shfl_sync(0xffffffffu, O[10], (lane & ~3) | 2);
  const float r0 = __fdividef(1.f, l0), r1 = __fdividef(1.f, l1);
#pragma unroll
  for (int c = 0; c < 3; c++)
    if (c < 2 || (lane & 3) < 2) {
      const int col = h * 20 + c * 8 + (lane & 3) * 2;
      uint32_t* o0 = (uint32_t*)g_o + o_line(row0, col >> 3) * 32 + (row0 & 7) * 4 + ((col & 7) >> 1);
      o0[0] = pack_bf16(O[4 * c] * r0, O[4 * c + 1] * r0);
      o0[256] = pack_bf16(O[4 * c + 2] * r1, O[4 * c + 3] * r1);
    }
}

struct alignas(64) AttParams {
  CUtensorMap b_w2;
  const unsigned int* norms;
  unsigned int *reset_a, *reset_b, *reset_c;
  const uint32_t* zeros;
  int jobs;
};
__global__ void __launch_bounds__(512, 1) att_kernel(const __grid_constant__ AttParams p) {
  const unsigned int* norms = p.norms;
  extern __shared__ __align__(1024) uint8_t smem[];
  const uint32_t sK = smem_u32(smem), sV = sK + ATT_V, bars = sK + ATT_BAR;
  const int h = blockIdx.x >> 2, qt = blockIdx.x & 3;
  const int tid = threadIdx.x, lane = tid & 31, wg = __shfl_sync(0xffffffffu, tid >> 7, 0), warp = (tid >> 5) & 3;
  if (tid == 0) {
    for (int c = 0; c < 9; c++) mbar_init(bars + c * 8, 1);
    asm volatile("fence.mbarrier_init.release.cluster;" ::: "memory");
  }
  *(uint32_t*)(smem + (tid >> 5) * KPITCH + 6144 + lane * 4) = 0u;
  asm volatile("fence.proxy.async;" ::: "memory");
  const uint32_t z0 = __ldg(p.zeros + (tid & 1)), z1 = __ldg(p.zeros + 2 + (tid & 1));
  __syncthreads();
  pdl_wait();
  pdl_launch();
  const uint8_t* gq = (const uint8_t*)g_qkv + (size_t)h * HEAD_BYTES;
  const uint64_t dK = mk_desc(sK, 128, 384, 0);
  const uint64_t dV = mk_desc(sV, 384, 128, 0);
  uint32_t q[6];
  auto load_q = [&](int row0) {
    const uint32_t* qa = (const uint32_t*)(gq + (row0 >> 3) * 384 + (row0 & 7) * 16) + (lane & 3);
    q[0] = __ldcg(qa); q[1] = __ldcg(qa + 96); q[2] = __ldcg(qa + 32); q[3] = __ldcg(qa + 128); q[4] = __ldcg(qa + 64); q[5] = __ldcg(qa + 160);
  };
  const int rowA = qt * 512 + wg * 64 + warp * 16 + (lane >> 2);
  load_q(rowA);
  auto load_kv = [&](int c) {
    mbar_expect_tx(bars + c * 8, 24576);
    bulk_g2s(sK + c * 2 * KPITCH, gq + 32 * HEAD_BYTES + c * 12288, 6144, bars + c * 8);
    bulk_g2s(sK + (c * 2 + 1) * KPITCH, gq + 32 * HEAD_BYTES + c * 12288 + 6144, 6144, bars + c * 8);
    bulk_g2s(sV + c * 12288, gq + 64 * HEAD_BYTES + c * 12288, 12288, bars + c * 8);
  };
  if (tid == 480) { load_kv(0); load_kv(1); }
  __syncwarp();
  auto load_rest = [&]() {
        if (tid == 480) {
#pragma unroll 1
          for (int c = 2; c < 8; c++) load_kv(c);
          if (p.jobs) {
            mbar_expect_tx(bars + 64, blockIdx.x < 16 ? 30720 : 15360);
#pragma unroll 1
            for (int job = blockIdx.x; job < 144; job += 128)
#pragma unroll 1
              for (int b = 0; b < 5; b++) tma_3d(sK + ATT_JOB + (job >> 7) * 15360 + b * 3072, &p.b_w2, b * 16, job / 18, (job % 18) * 96, bars + 64);
          }
        }
        __syncwarp();
  };
  const bool unsafe = !(__uint_as_float(__ldcg(norms + h)) * __uint_as_float(__ldcg(norms + 32 + h)) <= 3500.f);
  if (blockIdx.x == 0 && tid < NORM_OFF) { p.reset_a[tid] = 0u; if (tid < FLAG_SET - NORM_OFF) p.reset_b[tid] = 0u; if (p.reset_c) p.reset_c[tid] = 0u; }
  auto fast_tile = [&](auto first, int row0) -> bool {
      constexpr int tt = first.value ? 0 : 1;
      float S[64], O[12];
      uint32_t P[32];
#pragma unroll
      for (int k = 0; k < 64; k++) S[k] = 0.f;
#pragma unroll
      for (int k = 0; k < 12; k++) O[k] = 0.f;
      auto blocks = [&](int g0, int g1) {
        uint64_t gk = dK + g0 * (KPITCH / 16), gv = dV + g0 * 384;
#pragma unroll 1
        for (int g = g0; g < g1; g++) {
        if (tt == 0 && (g & 1) == 0) mbar_wait_warp(bars + (g >> 1) * 8, 0);
        wg_fence();
        wgmma_rs_n128<0>(S, q[0], q[1], q[2], q[3], gk, 0);
        wgmma_rs_n128<0>(S, q[4], q[5], z0, z1, gk + 16, 1);
        wg_commit();
        wg_wait<0>();
        fence_regs(S);
#pragma unroll
        for (int hf = 0; hf < 4; hf++) {
          constexpr int NB = 16 / 4;
          uint32_t (&Ph)[2 * NB] = *(uint32_t(*)[2 * NB])(P + hf * 2 * NB);
#pragma unroll
          for (int b = hf * NB; b < hf * NB + NB; b++) {
            if (is_mufu(b)) { P[2 * b] = pack_bf16(ex2(S[4 * b]), ex2(S[4 * b + 1])); P[2 * b + 1] = pack_bf16(ex2(S[4 * b + 2]), ex2(S[4 * b + 3])); }
            else { P[2 * b] = exp2_poly_pair(S[4 * b], S[4 * b + 1]); P[2 * b + 1] = exp2_poly_pair(S[4 * b + 2], S[4 * b + 3]); }
          }
          fence_regs(Ph);
          wg_fence();
#pragma unroll
          for (int s = hf * NB / 2; s < (hf + 1) * NB / 2; s++) wgmma_rs_n24<1>(O, P[4 * s], P[4 * s + 1], P[4 * s + 2], P[4 * s + 3], gv + s * 48, 1);
          wg_commit();
        }
        wg_wait<0>();
        gk += KPITCH / 16; gv += 384;
        }
      };
      if (tt == 0) {
        blocks(0, 2);
        load_rest();
        blocks(2, 16);
      } else blocks(0, 16);
      fence_regs(O);
      att_store(O, row0, h, lane);
      bool bad = false;
      float m = 0.f;
#pragma unroll
      for (int k = 0; k < 12; k++) { m = fmaxf(m, fabsf(O[k])); bad |= (O[k] != O[k]); }
      bad |= !(m <= 3e38f);
      if ((lane & 3) == 2) bad |= !(O[8] >= 0x1p-20f) || !(O[10] >= 0x1p-20f);
      uint32_t r;
      asm volatile("{\n.reg .pred p, r;\nsetp.ne.u32 p, %1, 0;\nbarrier.red.or.pred.aligned r, %2, 128, p;\nselp.u32 %0, 1, 0, r;\n}\n" : "=r"(r) : "r"((uint32_t)bad), "r"(1 + wg) : "memory");
      return r != 0;
  };
  auto safe_tile = [&](int row0) {
      float S[64], O[12];
      uint32_t P[32];
#pragma unroll
      for (int k = 0; k < 64; k++) S[k] = 0.f;
      if ((lane & 3) >= 2) { q[4] = 0u; q[5] = 0u; }
      float m0 = -INFINITY, m1 = -INFINITY;
#pragma unroll
      for (int k = 0; k < 12; k++) O[k] = 0.f;
      uint64_t gk = dK, gv = dV;
#pragma unroll 1
      for (int g = 0; g < 16; g++) {
        wg_fence();
        wgmma_rs_n128<0>(S, q[0], q[1], q[2], q[3], gk, 0);
        wgmma_rs_n128<0>(S, q[4], q[5], z0, z1, gk + 16, 1);
        wg_commit();
        wg_wait<0>();
        fence_regs(S);
        float x0 = m0, x1 = m1;
#pragma unroll
        for (int b = 0; b < 16; b++) {
          if (!is_mufu(b)) { S[4 * b] *= 0x1p22f; S[4 * b + 1] *= 0x1p22f; S[4 * b + 2] *= 0x1p22f; S[4 * b + 3] *= 0x1p22f; }
          x0 = fmaxf(x0, fmaxf(S[4 * b], S[4 * b + 1]));
          x1 = fmaxf(x1, fmaxf(S[4 * b + 2], S[4 * b + 3]));
        }
        x0 = fmaxf(x0, __shfl_xor_sync(0xffffffffu, x0, 1)); x1 = fmaxf(x1, __shfl_xor_sync(0xffffffffu, x1, 1));
        x0 = fmaxf(x0, __shfl_xor_sync(0xffffffffu, x0, 2)); x1 = fmaxf(x1, __shfl_xor_sync(0xffffffffu, x1, 2));
        const float al0 = ex2(m0 - x0), al1 = ex2(m1 - x1);
        m0 = x0; m1 = x1;
#pragma unroll
        for (int c = 0; c < 3; c++) { O[4 * c] *= al0; O[4 * c + 1] *= al0; O[4 * c + 2] *= al1; O[4 * c + 3] *= al1; }
#pragma unroll
        for (int b = 0; b < 16; b++) {
          P[2 * b] = pack_bf16(ex2(S[4 * b] - m0), ex2(S[4 * b + 1] - m0));
          P[2 * b + 1] = pack_bf16(ex2(S[4 * b + 2] - m1), ex2(S[4 * b + 3] - m1));
        }
        fence_regs(P);
        fence_regs(O);
        wg_fence();
#pragma unroll
        for (int s = 0; s < 8; s++) wgmma_rs_n24<1>(O, P[4 * s], P[4 * s + 1], P[4 * s + 2], P[4 * s + 3], gv + s * 48, 1);
        wg_commit();
        wg_wait<0>();
        fence_regs(O);
        gk += KPITCH / 16; gv += 384;
      }
      att_store(O, row0, h, lane);
      named_bar(1 + wg, 128);
  };
  bool redo = true;
  if (!__any_sync(0xffffffffu, unsafe)) redo = fast_tile(IC<1>{}, rowA);
  else {
    load_rest();
#pragma unroll 1
    for (int c = 0; c < 8; c++) mbar_wait(bars + c * 8, 0);
  }
  if (__any_sync(0xffffffffu, redo)) safe_tile(rowA);
  load_q(rowA + 256);
  if (tid == 480 && p.jobs) {
    mbar_wait(bars + 64, 0);
#pragma unroll 1
    for (int job = blockIdx.x; job < 144; job += 128) bulk_s2g(g_wt + WT_W2 + job * 15360, sK + ATT_JOB + (job >> 7) * 15360, 15360);
  }
  __syncwarp();
  redo = true;
  if (!__any_sync(0xffffffffu, unsafe)) redo = fast_tile(IC<0>{}, rowA + 256);
  if (__any_sync(0xffffffffu, redo)) safe_tile(rowA + 256);
  if (tid == 480) asm volatile("cp.async.bulk.wait_group 0;" ::: "memory");
}

typedef CUresult (*EncodeFn)(CUtensorMap*, CUtensorMapDataType, cuuint32_t, void*, const cuuint64_t*, const cuuint64_t*, const cuuint32_t*,
                             const cuuint32_t*, CUtensorMapInterleave, CUtensorMapSwizzle, CUtensorMapL2promotion, CUtensorMapFloatOOBfill);

static void make_a(EncodeFn enc, CUtensorMap* m, const void* ptr, int K) {
  cuuint64_t dims[2] = {(cuuint64_t)K, (cuuint64_t)SEQ}, strides[1] = {(cuuint64_t)K * 2};
  cuuint32_t box[2] = {64, 128}, es[2] = {1, 1};
  enc(m, CU_TENSOR_MAP_DATA_TYPE_BFLOAT16, 2, (void*)ptr, dims, strides, box, es, CU_TENSOR_MAP_INTERLEAVE_NONE, CU_TENSOR_MAP_SWIZZLE_128B,
      CU_TENSOR_MAP_L2_PROMOTION_NONE, CU_TENSOR_MAP_FLOAT_OOB_FILL_NONE);
}
static void make_out(EncodeFn enc, CUtensorMap* m, void* ptr) {
  cuuint64_t dims[2] = {(cuuint64_t)DM, (cuuint64_t)SEQ}, strides[1] = {(cuuint64_t)DM * 2};
  cuuint32_t box[2] = {80, 64}, es[2] = {1, 1};
  enc(m, CU_TENSOR_MAP_DATA_TYPE_BFLOAT16, 2, ptr, dims, strides, box, es, CU_TENSOR_MAP_INTERLEAVE_NONE, CU_TENSOR_MAP_SWIZZLE_NONE,
      CU_TENSOR_MAP_L2_PROMOTION_NONE, CU_TENSOR_MAP_FLOAT_OOB_FILL_NONE);
}
static void make_b(EncodeFn enc, CUtensorMap* m, const void* ptr, int K, int N, int BN, int bk, int bw) {
  cuuint64_t dims[3] = {(cuuint64_t)BN, (cuuint64_t)(N / BN), (cuuint64_t)K}, strides[2] = {(cuuint64_t)BN * 2, (cuuint64_t)N * 2};
  cuuint32_t box[3] = {(cuuint32_t)bw, 1, (cuuint32_t)bk}, es[3] = {1, 1, 1};
  enc(m, CU_TENSOR_MAP_DATA_TYPE_BFLOAT16, 3, (void*)ptr, dims, strides, box, es, CU_TENSOR_MAP_INTERLEAVE_NONE, bw == 64 ? CU_TENSOR_MAP_SWIZZLE_128B : CU_TENSOR_MAP_SWIZZLE_32B,
      CU_TENSOR_MAP_L2_PROMOTION_NONE, CU_TENSOR_MAP_FLOAT_OOB_FILL_NONE);
}
template <typename... KArgs, typename... Args>
static void launch(void (*kern)(KArgs...), int grid, int threads, int smem, bool pdl, Args... args) {
  cudaFuncSetAttribute(kern, cudaFuncAttributeMaxDynamicSharedMemorySize, smem);
  cudaLaunchConfig_t cfg = {};
  cfg.gridDim = dim3(grid); cfg.blockDim = dim3(threads); cfg.dynamicSmemBytes = smem; cfg.stream = cudaStreamPerThread;
  cudaLaunchAttribute at[1];
  at[0].id = cudaLaunchAttributeProgrammaticStreamSerialization; at[0].val.programmaticStreamSerializationAllowed = 1;
  cfg.attrs = at; cfg.numAttrs = pdl ? 1 : 0;
  cudaLaunchKernelEx(&cfg, kern, KArgs(args)...);
}

static void make_pref(signed char* pref, int ntpc) {
  auto kern = chain_kernel<PH_WO | PH_W1 | PH_W2, false, true>;
  cudaFuncSetAttribute(kern, cudaFuncAttributeMaxDynamicSharedMemorySize, CHAIN_SMEM);
  cudaFuncSetAttribute(kern, cudaFuncAttributeNonPortableClusterSizeAllowed, 1);
  int n[10] = {0};
  for (int t = 2; t <= 8; t++) {
    cudaLaunchConfig_t cfg = {};
    cfg.gridDim = dim3(2 * t * 16); cfg.blockDim = dim3(CHAIN_THREADS); cfg.dynamicSmemBytes = CHAIN_SMEM;
    cudaLaunchAttribute at[1];
    at[0].id = cudaLaunchAttributeClusterDimension; at[0].val.clusterDim.x = 2 * t; at[0].val.clusterDim.y = 1; at[0].val.clusterDim.z = 1;
    cfg.attrs = at; cfg.numAttrs = 1;
    if (cudaOccupancyMaxActiveClusters(&n[t], kern, &cfg) != cudaSuccess) { n[t] = -1; cudaGetLastError(); }
  }
  int best[10] = {0}, cnt[10], found = 0;
  for (int code = 0; code < 1000000 && !found; code++) {
    int c = code, tot = 0, g = 0;
    for (int m = 0; m < 10; m++) cnt[m] = 0;
    for (int m = 4; m <= 9; m++) { cnt[m] = c % 10; c /= 10; tot += cnt[m] * m; g += cnt[m]; }
    if (g > 9 || tot > ntpc) continue;
    bool ok = true;
    for (int t = 3; t <= 8 && ok; t++) { int s = 0; for (int m = 4; m <= 9; m++) s += cnt[m] * (m / t); ok = (s == n[t]); }
    if (ok) { found = 1; for (int m = 0; m < 10; m++) best[m] = cnt[m]; }
  }
  int grp[80], size[10], ng = 0, id = 0;
  for (int t = 0; t < 80; t++) { grp[t] = -1; pref[2 * t] = pref[2 * t + 1] = -1; }
  if (found) {
    for (int m = 4; m <= 9; m++) for (int k = 0; k < best[m]; k++) size[ng++] = m;
    for (int r = 0; r < 9; r++) for (int g = 0; g < ng; g++) if (size[g] > r && id < ntpc) grp[id++] = g;
  }
  int nb = 0;
  bool used[80] = {false};
  auto put = [&](int t, int blk, int w) {
    const int tile = blk * 16 + w * 2;
    pref[2 * t] = (signed char)tile; pref[2 * t + 1] = (signed char)(tile + 1); used[t] = true;
  };
  for (int g = 0; g < ng && nb < 8; g++)
    if (size[g] >= 8) {
      int w = 0;
      for (int t = 0; t < ntpc && w < 8; t++) if (grp[t] == g) put(t, nb, w++);
      nb++;
    }
  int pos = nb * 8;
  for (int pass = 0; pass < 2; pass++)
    for (int g = 0; g <= ng; g++)
      for (int t = 0; t < ntpc && pos < 64; t++)
        if (!used[t] && (g < ng ? (grp[t] == g && (size[g] < 8) == (pass == 0)) : (pass == 1 && grp[t] < 0))) { put(t, pos >> 3, pos & 7); pos++; }
}

extern "C" void kernel_launch(void* const* d_in, const int* in_sizes, int n_in, void* d_out, int out_size) {
  const bf16* x = (const bf16*)d_in[0];
  const bf16* wqkv = (const bf16*)d_in[1];
  const bf16* wo = (const bf16*)d_in[2];
  const bf16* w1 = (const bf16*)d_in[4];
  const bf16* b1 = (const bf16*)d_in[5];
  const bf16* w2 = (const bf16*)d_in[6];
  const bf16* b2 = (const bf16*)d_in[7];
  void* fn = nullptr;
  cudaDriverEntryPointQueryResult qr;
  cudaGetDriverEntryPoint("cuTensorMapEncodeTiled", &fn, cudaEnableDefault, &qr);
  EncodeFn enc = (EncodeFn)fn;
  void *px0, *px2, *pf, *pz;
  cudaGetSymbolAddress(&px0, g_x0);
  cudaGetSymbolAddress(&px2, g_x2); cudaGetSymbolAddress(&pf, g_s);
  unsigned int* flags = ((Small*)pf)->flags;
  pz = ((Small*)pf)->zeros;

  int nsm = 132;
  cudaDeviceGetAttribute(&nsm, cudaDevAttrMultiProcessorCount, 0);
  const int ngrid = nsm >= 128 ? (nsm > 160 ? 160 : (nsm & ~1)) : 128;
  ChainParams p;
  make_pref(p.pref, ngrid / 2);
  make_a(enc, &p.a_x, x, DM);
  make_out(enc, &p.o_out, d_out);
  AttParams ap;
  make_b(enc, &p.b_wo, wo, DM, DM, 80, 64, 16); make_b(enc, &p.b_w1, w1, DM, FF, 216, 64, 16); make_b(enc, &ap.b_w2, w2, FF, DM, 80, 96, 16);
  ap.zeros = (const uint32_t*)pz;
  make_b(enc, &p.b_wqkv, wqkv, DM, 1920, 120, 64, 64);
  p.xres = (const bf16*)px0; p.xin = x; p.b1 = b1; p.b2 = b2; p.flags = flags;

  launch(chain_kernel<PH_QKV, true, false>, ngrid, CHAIN_THREADS, CHAIN_SMEM, false, p);
  ap.norms = flags + NORM_OFF; ap.reset_a = flags; ap.reset_b = flags + FLAG_SET + NORM_OFF; ap.reset_c = flags + 2 * FLAG_SET; ap.jobs = 1;
  launch(att_kernel, 128, 512, ATT_SMEM, true, ap);
  p.flags = flags + FLAG_SET;
  launch(chain_kernel<PH_WO | PH_W1 | PH_W2 | PH_QKV, false, false>, ngrid, CHAIN_THREADS, CHAIN_SMEM, true, p);
  ap.norms = flags + FLAG_SET + NORM_OFF; ap.reset_a = flags + FLAG_SET; ap.reset_b = flags + NORM_OFF; ap.reset_c = nullptr; ap.jobs = 0;
  launch(att_kernel, 128, 512, ATT_SMEM, true, ap);
  p.xres = (const bf16*)px2; p.flags = flags + 2 * FLAG_SET;
  launch(chain_kernel<PH_WO | PH_W1 | PH_W2, false, true>, ngrid, CHAIN_THREADS, CHAIN_SMEM, true, p);
}
```
